```python
import torch

def _softmax(x, axis=-1):
    return torch.softmax(x, dim=axis)
def _gelu(x):
    return torch.nn.functional.gelu(x, approximate="tanh")
def _silu(x):
    return torch.nn.functional.silu(x)
def _sigmoid(x):
    return torch.sigmoid(x)
def _layernorm(x, axis=-1, eps=1e-5):
    m = x.mean(dim=axis, keepdim=True)
    v = x.var(dim=axis, keepdim=True, unbiased=False)
    return (x - m) / torch.sqrt(v + eps)
def _scatter_add(tgt, idx, src, axis=0):
    return tgt.clone().index_add_(axis, idx, src)
def _segment_sum(src, seg, n):
    out = torch.zeros((n,) + src.shape[1:], dtype=src.dtype)
    return out.index_add_(0, seg, src)
def _pad(x, pw):
    flat = tuple(v for pair in reversed(pw) for v in pair)
    return torch.nn.functional.pad(x, flat)

kernel_name = 'gated_mix__ssm_conv_s4d__dense_activation_relu__prompt'

def setup_inputs():

    _w = (lambda a: (lambda t: t.to(torch.bfloat16) if t.is_floating_point() else t)(torch.as_tensor(a)))
    def _A_setup():
        Bsz, L, D, N = 1, 2048, 640, 128
        return {
            "u": _w((lambda *s: torch.randn(*s, dtype=torch.bfloat16) * 0.05)(Bsz, L, D)),
            "log_A_real": _w((lambda *s: torch.randn(*s, dtype=torch.bfloat16) * 6.4)(D, N) * 0.5),
            "A_imag": _w((lambda *s: torch.randn(*s, dtype=torch.bfloat16) * 0.2)(D, N) * 3.14),
            "C_real": _w((lambda *s: torch.randn(*s, dtype=torch.bfloat16) * 0.8)(D, N) / N ** 0.5),
            "C_imag": _w((lambda *s: torch.randn(*s, dtype=torch.bfloat16) * 0.8)(D, N) / N ** 0.5),
            "log_dt": _w((lambda *s: torch.randn(*s, dtype=torch.bfloat16) * 0.2)(D) * 0.5 - 4.0),
            "D_skip": _w((lambda *s: torch.randn(*s, dtype=torch.bfloat16) * 0.2)(D)),
        }
    _A_in = _A_setup()

    def _B_setup():
        B, S, D, Dff = 1, 2048, 640, 1728
        return {
            "x": _w((lambda *s: torch.randn(*s, dtype=torch.bfloat16) * 0.05)(B, S, D)),
            "w1": _w((lambda *s: torch.randn(*s, dtype=torch.bfloat16) * 0.05)(D, Dff)),
            "w2": _w((lambda *s: torch.randn(*s, dtype=torch.bfloat16) * 0.05)(Dff, D)),
        }
    _B_in = _B_setup()

    return {
        "A_u": _A_in["u"],
        "A_log_A_real": _A_in["log_A_real"],
        "A_A_imag": _A_in["A_imag"],
        "A_C_real": _A_in["C_real"],
        "A_C_imag": _A_in["C_imag"],
        "A_log_dt": _A_in["log_dt"],
        "A_D_skip": _A_in["D_skip"],
        "B_x": _B_in["x"],
        "B_w1": _B_in["w1"],
        "B_w2": _B_in["w2"],
        "gate_w": _w((lambda *s: torch.randn(*s, dtype=torch.bfloat16) * 0.05)(640) * 16.0),
    }

def reference(A_u, A_log_A_real, A_A_imag, A_C_real, A_C_imag, A_log_dt, A_D_skip, B_x, B_w1, B_w2, gate_w):
    def _A_ref(u, log_A_real, A_imag, C_real, C_imag, log_dt, D_skip):
        L = u.shape[1]
        dt = torch.exp(log_dt)
        A = -torch.exp(log_A_real) + 1j * A_imag
        C = (C_real + 1j * C_imag) * dt[:, None]
        pos = (lambda x, dt: x.to(dt))(torch.arange(L), log_dt.dtype)
        P = torch.exp((A * dt[:, None])[:, :, None] * pos[None, None, :])
        K = 2.0 * torch.einsum("dn,dnl->dl", C, P).real
        L2 = 2 * L
        u_t = (lambda x, *d: x.permute(*d))(u, 0, 2, 1)
        Kf = (lambda x, *a, **k: torch.fft.rfft(x.float(), *a, **k))(K, L2)
        Uf = (lambda x, *a, **k: torch.fft.rfft(x.float(), *a, **k))(u_t, L2)
        y = (lambda x, *a, **k: torch.fft.irfft(x, *a, **k).to(torch.bfloat16))(Uf * Kf[None, :, :], L2)[:, :, :L]
        y = (lambda x, *d: x.permute(*d))(y, 0, 2, 1)
        return y + u * D_skip[None, None, :]

    def _B_ref(x, w1, w2):
        h = torch.einsum("bsd,df->bsf", x, w1)
        zero = torch.zeros_like(h)
        h = torch.maximum(h, zero)
        return torch.einsum("bsf,fd->bsd", h, w2)

    x = A_u
    g = _sigmoid((x * gate_w).sum(-1, keepdims=True))
    a = _A_ref(x, A_log_A_real, A_A_imag, A_C_real, A_C_imag, A_log_dt, A_D_skip)
    b = _B_ref(x, B_w1, B_w2)
    return g * a + (1 - g) * b
```

```cpp
#include <cuda_runtime.h>
#include <cuda_bf16.h>
#include <cuda.h>
#include <stdint.h>

namespace {

constexpr int L_ = 2048, D_ = 640, F_ = 1728, NMODE = 128;
constexpr int NCTA = 128;
constexpr int NTHREADS = 512;

constexpr int BN1 = 216, S1 = 3, NK1 = D_ / 64;
constexpr int A1_BYTES = 128 * 128;
constexpr int B1_BLK = 64 * 64;
constexpr int B1_BYTES = 7 * B1_BLK;
constexpr int ST1_BYTES = A1_BYTES + B1_BYTES;
constexpr int S2 = 5, NK2 = F_ / 64;
constexpr int A2_BYTES = 128 * 128;
constexpr int B2_BLK = 64 * 32;
constexpr int B2_BYTES = 5 * B2_BLK;
constexpr int ST2_BYTES = A2_BYTES + B2_BYTES;
constexpr int OFF_RING = 0;
constexpr int RING_BYTES = S1 * ST1_BYTES;
constexpr int HST_PITCH = BN1 * 2;
constexpr int Q_WORDS = 64 + 2048 + 32;
constexpr int Q_BYTES = Q_WORDS * 4;
constexpr int OFF_Q = RING_BYTES;
constexpr int PL_STRIDE = 41 * 16;
constexpr int PLCH_BYTES = 8 * PL_STRIDE;
constexpr int OFF_PL = OFF_Q + 5 * Q_BYTES;
constexpr int SLAB_PITCH = 1296;
constexpr int OFF_KG = OFF_PL + 5 * PLCH_BYTES;
constexpr int KG_BYTES = 4608;
constexpr int KG_PITCH = 144;
constexpr int OFF_BAR = OFF_KG + 5 * KG_BYTES;
constexpr int SMEM_USED = OFF_BAR + 256;
constexpr int SMEM_BYTES = SMEM_USED + 1024;
static_assert(SMEM_BYTES <= 232448, "smem");
static_assert(S2 * ST2_BYTES <= RING_BYTES, "ring");
static_assert(16 * SLAB_PITCH <= 5 * PLCH_BYTES, "slab");
static_assert(OFF_Q % 1024 == 0, "align");
static_assert(OFF_PL % 128 == 0 && OFF_KG % 16 == 0 && OFF_BAR % 8 == 0, "align");

enum {
  BAR_FULL1 = 0, BAR_EMPTY1 = BAR_FULL1 + S1, BAR_FULL2 = BAR_EMPTY1 + S1, BAR_EMPTY2 = BAR_FULL2 + S2,
  BAR_RINGFREE = BAR_EMPTY2 + S2, BAR_SLAB, BAR_UFULL, BAR_QREADY, BAR_CONVDONE = BAR_QREADY + 5, BAR_AFULL, BAR_COUNT
};
static_assert(BAR_COUNT * 8 <= 256, "bars");

__device__ __align__(1024) __nv_bfloat16 g_h[L_ * F_];
__device__ __align__(1024) __nv_bfloat16 g_up[D_ * L_];
__device__ __align__(1024) __nv_bfloat16 g_aT[D_ * L_];
__device__ __align__(1024) float g_gate[L_];
__device__ unsigned g_flag_u[NCTA];
__device__ unsigned g_flag_h[NCTA * 2];
__device__ unsigned g_flag_a[NCTA * 2];
__device__ unsigned g_epoch;
__device__ unsigned g_done;

constexpr long long WAIT_LIMIT = 100000000LL;
__device__ __forceinline__ uint32_t smem_u32(const void* p) { return (uint32_t)__cvta_generic_to_shared(p); }
__device__ __forceinline__ void mbar_init(uint32_t bar, int cnt) {
  asm volatile("mbarrier.init.shared::cta.b64 [%0], %1;" ::"r"(bar), "r"(cnt) : "memory");
}
__device__ __forceinline__ void mbar_expect_tx(uint32_t bar, int bytes) {
  asm volatile("mbarrier.arrive.expect_tx.shared::cta.b64 _, [%0], %1;" ::"r"(bar), "r"(bytes) : "memory");
}
__device__ __forceinline__ void mbar_arrive(uint32_t bar) {
  asm volatile("mbarrier.arrive.shared::cta.b64 _, [%0];" ::"r"(bar) : "memory");
}
__device__ __forceinline__ void mbar_arrive_cta(uint32_t bar, uint32_t cta) {
  asm volatile("{\n.reg .b32 ra;\nmapa.shared::cluster.u32 ra, %0, %1;\n"
               "mbarrier.arrive.shared::cluster.b64 _, [ra];\n}\n" ::"r"(bar), "r"(cta) : "memory");
}
__device__ __forceinline__ bool mbar_try(uint32_t bar, int parity) {
  uint32_t ok;
  asm volatile("{\n.reg .pred p;\nmbarrier.try_wait.parity.shared::cta.b64 p, [%1], %2;\nselp.u32 %0, 1, 0, p;\n}\n"
               : "=r"(ok) : "r"(bar), "r"(parity) : "memory");
  return ok != 0;
}
__device__ __forceinline__ void mbar_wait(uint32_t bar, int parity) {
  if (mbar_try(bar, parity)) return;
  const long long t0 = clock64();
  while (!mbar_try(bar, parity)) {
    if (clock64() - t0 > WAIT_LIMIT) break;
  }
}
__device__ __forceinline__ unsigned ld_acquire(const unsigned* p) {
  unsigned v;
  asm volatile("ld.acquire.gpu.global.u32 %0, [%1];" : "=r"(v) : "l"(p) : "memory");
  return v;
}
__device__ __forceinline__ void st_release(unsigned* p, unsigned v) {
  asm volatile("st.release.gpu.global.u32 [%0], %1;" ::"l"(p), "r"(v) : "memory");
}
__device__ __forceinline__ void wait_flag(const unsigned* p, unsigned tag) {
  if (ld_acquire(p) == tag) return;
  const long long t0 = clock64();
  while (ld_acquire(p) != tag) {
    if (clock64() - t0 > WAIT_LIMIT) break;
    __nanosleep(20);
  }
}
__device__ __forceinline__ void fence_async() { asm volatile("fence.proxy.async;" ::: "memory"); }
__device__ __forceinline__ void fence_async_smem() { asm volatile("fence.proxy.async.shared::cta;" ::: "memory"); }
__device__ __forceinline__ void named_sync(int id, int n) { asm volatile("bar.sync %0, %1;" ::"r"(id), "r"(n) : "memory"); }

__device__ __forceinline__ void tma_ld2(uint32_t dst, const CUtensorMap* m, uint32_t bar, int c0, int c1) {
  asm volatile("cp.async.bulk.tensor.2d.shared::cluster.global.mbarrier::complete_tx::bytes [%0], [%1, {%3, %4}], [%2];"
               ::"r"(dst), "l"(m), "r"(bar), "r"(c0), "r"(c1) : "memory");
}
__device__ __forceinline__ void tma_ld2_mc(uint32_t dst, const CUtensorMap* m, uint32_t bar, int c0, int c1) {
  asm volatile("cp.async.bulk.tensor.2d.shared::cluster.global.mbarrier::complete_tx::bytes.multicast::cluster "
               "[%0], [%1, {%3, %4}], [%2], %5;"
               ::"r"(dst), "l"(m), "r"(bar), "r"(c0), "r"(c1), "h"((uint16_t)3) : "memory");
}
__device__ __forceinline__ void tma_ld3(uint32_t dst, const CUtensorMap* m, uint32_t bar, int c0, int c1, int c2) {
  asm volatile("cp.async.bulk.tensor.3d.shared::cluster.global.mbarrier::complete_tx::bytes [%0], [%1, {%3, %4, %5}], [%2];"
               ::"r"(dst), "l"(m), "r"(bar), "r"(c0), "r"(c1), "r"(c2) : "memory");
}
__device__ __forceinline__ void tma_st2(const CUtensorMap* m, uint32_t src, int c0, int c1) {
  asm volatile("cp.async.bulk.tensor.2d.global.shared::cta.bulk_group [%0, {%2, %3}], [%1];"
               ::"l"(m), "r"(src), "r"(c0), "r"(c1) : "memory");
}
__device__ __forceinline__ void bulk_ld(uint32_t dst, const void* src, int bytes, uint32_t bar) {
  asm volatile("cp.async.bulk.shared::cluster.global.mbarrier::complete_tx::bytes [%0], [%1], %2, [%3];"
               ::"r"(dst), "l"(src), "r"(bytes), "r"(bar) : "memory");
}
__device__ __forceinline__ void bulk_commit() { asm volatile("cp.async.bulk.commit_group;" ::: "memory"); }
__device__ __forceinline__ void bulk_wait_read() { asm volatile("cp.async.bulk.wait_group.read 0;" ::: "memory"); }
__device__ __forceinline__ void bulk_wait_all() { asm volatile("cp.async.bulk.wait_group 0;" ::: "memory"); }

__device__ __forceinline__ void wg_fence() { asm volatile("wgmma.fence.sync.aligned;" ::: "memory"); }
__device__ __forceinline__ void wg_commit() { asm volatile("wgmma.commit_group.sync.aligned;" ::: "memory"); }
template <int N> __device__ __forceinline__ void wg_wait() { asm volatile("wgmma.wait_group.sync.aligned %0;" ::"n"(N) : "memory"); }
__device__ __forceinline__ uint64_t mkdesc(uint32_t addr, uint32_t lbo, uint32_t sbo, int swz) {
  return (uint64_t)((addr & 0x3FFFF) >> 4) | ((uint64_t)(lbo >> 4) << 16) | ((uint64_t)(sbo >> 4) << 32) | ((uint64_t)swz << 62);
}
template <int N> __device__ __forceinline__ void reg_fence(float (&d)[N]) {
#pragma unroll
  for (int i = 0; i < N; i++) asm volatile("" : "+f"(d[i])::"memory");
}

__device__ __forceinline__ void wgmma_ss_n128_tb(float (&d)[108], uint64_t da, uint64_t db, int sc) {
  asm volatile("{\n.reg .pred p;\nsetp.ne.b32 p, %66, 0;\n"
    "wgmma.mma_async.sync.aligned.m64n128k16.f32.bf16.bf16 "
    "{%0, %1, %2, %3, %4, %5, %6, %7, %8, %9, %10, %11, %12, %13, %14, %15, %16, %17, %18, %19, %20, %21, %22, %23, %24, %25, %26, %27, %28, %29, %30, %31, %32, %33, %34, %35, %36, %37, %38, %39, %40, %41, %42, %43, %44, %45, %46, %47, %48, %49, %50, %51, %52, %53, %54, %55, %56, %57, %58, %59, %60, %61, %62, %63}, "
    "%64, %65, p, 1, 1, 0, 1;\n}\n"
    : "+f"(d[0]), "+f"(d[1]), "+f"(d[2]), "+f"(d[3]), "+f"(d[4]), "+f"(d[5]), "+f"(d[6]), "+f"(d[7]), "+f"(d[8]), "+f"(d[9]), "+f"(d[10]), "+f"(d[11]), "+f"(d[12]), "+f"(d[13]), "+f"(d[14]), "+f"(d[15]), "+f"(d[16]), "+f"(d[17]), "+f"(d[18]), "+f"(d[19]), "+f"(d[20]), "+f"(d[21]), "+f"(d[22]), "+f"(d[23]), "+f"(d[24]), "+f"(d[25]), "+f"(d[26]), "+f"(d[27]), "+f"(d[28]), "+f"(d[29]), "+f"(d[30]), "+f"(d[31]), "+f"(d[32]), "+f"(d[33]), "+f"(d[34]), "+f"(d[35]), "+f"(d[36]), "+f"(d[37]), "+f"(d[38]), "+f"(d[39]), "+f"(d[40]), "+f"(d[41]), "+f"(d[42]), "+f"(d[43]), "+f"(d[44]), "+f"(d[45]), "+f"(d[46]), "+f"(d[47]), "+f"(d[48]), "+f"(d[49]), "+f"(d[50]), "+f"(d[51]), "+f"(d[52]), "+f"(d[53]), "+f"(d[54]), "+f"(d[55]), "+f"(d[56]), "+f"(d[57]), "+f"(d[58]), "+f"(d[59]), "+f"(d[60]), "+f"(d[61]), "+f"(d[62]), "+f"(d[63])
    : "l"(da), "l"(db), "r"(sc));
}
__device__ __forceinline__ void wgmma_ss_n88_tb(float (&d)[108], uint64_t da, uint64_t db, int sc) {
  asm volatile("{\n.reg .pred p;\nsetp.ne.b32 p, %46, 0;\n"
    "wgmma.mma_async.sync.aligned.m64n88k16.f32.bf16.bf16 "
    "{%0, %1, %2, %3, %4, %5, %6, %7, %8, %9, %10, %11, %12, %13, %14, %15, %16, %17, %18, %19, %20, %21, %22, %23, %24, %25, %26, %27, %28, %29, %30, %31, %32, %33, %34, %35, %36, %37, %38, %39, %40, %41, %42, %43}, "
    "%44, %45, p, 1, 1, 0, 1;\n}\n"
    : "+f"(d[64]), "+f"(d[65]), "+f"(d[66]), "+f"(d[67]), "+f"(d[68]), "+f"(d[69]), "+f"(d[70]), "+f"(d[71]), "+f"(d[72]), "+f"(d[73]), "+f"(d[74]), "+f"(d[75]), "+f"(d[76]), "+f"(d[77]), "+f"(d[78]), "+f"(d[79]), "+f"(d[80]), "+f"(d[81]), "+f"(d[82]), "+f"(d[83]), "+f"(d[84]), "+f"(d[85]), "+f"(d[86]), "+f"(d[87]), "+f"(d[88]), "+f"(d[89]), "+f"(d[90]), "+f"(d[91]), "+f"(d[92]), "+f"(d[93]), "+f"(d[94]), "+f"(d[95]), "+f"(d[96]), "+f"(d[97]), "+f"(d[98]), "+f"(d[99]), "+f"(d[100]), "+f"(d[101]), "+f"(d[102]), "+f"(d[103]), "+f"(d[104]), "+f"(d[105]), "+f"(d[106]), "+f"(d[107])
    : "l"(da), "l"(db), "r"(sc));
}
__device__ __forceinline__ void wgmma_ss_n80_tb(float (&d)[40], uint64_t da, uint64_t db, int sc) {
  asm volatile("{\n.reg .pred p;\nsetp.ne.b32 p, %42, 0;\n"
    "wgmma.mma_async.sync.aligned.m64n80k16.f32.bf16.bf16 "
    "{%0, %1, %2, %3, %4, %5, %6, %7, %8, %9, %10, %11, %12, %13, %14, %15, %16, %17, %18, %19, %20, %21, %22, %23, %24, %25, %26, %27, %28, %29, %30, %31, %32, %33, %34, %35, %36, %37, %38, %39}, "
    "%40, %41, p, 1, 1, 0, 1;\n}\n"
    : "+f"(d[0]), "+f"(d[1]), "+f"(d[2]), "+f"(d[3]), "+f"(d[4]), "+f"(d[5]), "+f"(d[6]), "+f"(d[7]), "+f"(d[8]), "+f"(d[9]), "+f"(d[10]), "+f"(d[11]), "+f"(d[12]), "+f"(d[13]), "+f"(d[14]), "+f"(d[15]), "+f"(d[16]), "+f"(d[17]), "+f"(d[18]), "+f"(d[19]), "+f"(d[20]), "+f"(d[21]), "+f"(d[22]), "+f"(d[23]), "+f"(d[24]), "+f"(d[25]), "+f"(d[26]), "+f"(d[27]), "+f"(d[28]), "+f"(d[29]), "+f"(d[30]), "+f"(d[31]), "+f"(d[32]), "+f"(d[33]), "+f"(d[34]), "+f"(d[35]), "+f"(d[36]), "+f"(d[37]), "+f"(d[38]), "+f"(d[39])
    : "l"(da), "l"(db), "r"(sc));
}
__device__ __forceinline__ void wgmma_rs_n32(float (&d)[16], uint32_t a0, uint32_t a1, uint32_t a2, uint32_t a3, uint64_t db, int sc) {
  asm volatile("{\n.reg .pred p;\nsetp.ne.b32 p, %21, 0;\n"
    "wgmma.mma_async.sync.aligned.m64n32k16.f32.bf16.bf16 "
    "{%0, %1, %2, %3, %4, %5, %6, %7, %8, %9, %10, %11, %12, %13, %14, %15}, {%16, %17, %18, %19}, %20, p, 1, 1, 0;\n}\n"
    : "+f"(d[0]), "+f"(d[1]), "+f"(d[2]), "+f"(d[3]), "+f"(d[4]), "+f"(d[5]), "+f"(d[6]), "+f"(d[7]), "+f"(d[8]), "+f"(d[9]), "+f"(d[10]), "+f"(d[11]), "+f"(d[12]), "+f"(d[13]), "+f"(d[14]), "+f"(d[15])
    : "r"(a0), "r"(a1), "r"(a2), "r"(a3), "l"(db), "r"(sc));
}
__device__ __forceinline__ void wgmma_rs_n24(float (&d)[16], uint32_t a0, uint32_t a1, uint32_t a2, uint32_t a3, uint64_t db, int sc) {
  asm volatile("{\n.reg .pred p;\nsetp.ne.b32 p, %17, 0;\n"
    "wgmma.mma_async.sync.aligned.m64n24k16.f32.bf16.bf16 "
    "{%0, %1, %2, %3, %4, %5, %6, %7, %8, %9, %10, %11}, {%12, %13, %14, %15}, %16, p, 1, 1, 0;\n}\n"
    : "+f"(d[0]), "+f"(d[1]), "+f"(d[2]), "+f"(d[3]), "+f"(d[4]), "+f"(d[5]), "+f"(d[6]), "+f"(d[7]), "+f"(d[8]), "+f"(d[9]), "+f"(d[10]), "+f"(d[11])
    : "r"(a0), "r"(a1), "r"(a2), "r"(a3), "l"(db), "r"(sc));
}
__device__ __forceinline__ void wgmma_rs_n16(float (&d)[16], uint32_t a0, uint32_t a1, uint32_t a2, uint32_t a3, uint64_t db, int sc) {
  asm volatile("{\n.reg .pred p;\nsetp.ne.b32 p, %13, 0;\n"
    "wgmma.mma_async.sync.aligned.m64n16k16.f32.bf16.bf16 "
    "{%0, %1, %2, %3, %4, %5, %6, %7}, {%8, %9, %10, %11}, %12, p, 1, 1, 0;\n}\n"
    : "+f"(d[0]), "+f"(d[1]), "+f"(d[2]), "+f"(d[3]), "+f"(d[4]), "+f"(d[5]), "+f"(d[6]), "+f"(d[7])
    : "r"(a0), "r"(a1), "r"(a2), "r"(a3), "l"(db), "r"(sc));
}
__device__ __forceinline__ void wgmma_rs_n8(float (&d)[16], uint32_t a0, uint32_t a1, uint32_t a2, uint32_t a3, uint64_t db, int sc) {
  asm volatile("{\n.reg .pred p;\nsetp.ne.b32 p, %9, 0;\n"
    "wgmma.mma_async.sync.aligned.m64n8k16.f32.bf16.bf16 "
    "{%0, %1, %2, %3}, {%4, %5, %6, %7}, %8, p, 1, 1, 0;\n}\n"
    : "+f"(d[0]), "+f"(d[1]), "+f"(d[2]), "+f"(d[3])
    : "r"(a0), "r"(a1), "r"(a2), "r"(a3), "l"(db), "r"(sc));
}

__device__ __forceinline__ uint32_t pack_bf16(float lo, float hi) {
  uint32_t r;
  asm("cvt.rn.bf16x2.f32 %0, %1, %2;" : "=r"(r) : "f"(hi), "f"(lo));
  return r;
}
__device__ __forceinline__ uint32_t pack_bf16_relu(float lo, float hi) {
  uint32_t r;
  asm("cvt.rn.relu.bf16x2.f32 %0, %1, %2;" : "=r"(r) : "f"(hi), "f"(lo));
  return r;
}
__device__ __forceinline__ uint32_t bmul2(uint32_t a, uint32_t b) {
  uint32_t r;
  asm("mul.rn.bf16x2 %0, %1, %2;" : "=r"(r) : "r"(a), "r"(b));
  return r;
}
__device__ __forceinline__ uint32_t badd2(uint32_t a, uint32_t b) {
  uint32_t r;
  asm("add.rn.bf16x2 %0, %1, %2;" : "=r"(r) : "r"(a), "r"(b));
  return r;
}
__device__ __forceinline__ float bf_lo(uint32_t w) { return __uint_as_float(w << 16); }
__device__ __forceinline__ float bf_hi(uint32_t w) { return __uint_as_float(w & 0xffff0000u); }
__device__ __forceinline__ float bf16r(float x) { return __bfloat162float(__float2bfloat16_rn(x)); }
__device__ __forceinline__ float ldbf(const __nv_bfloat16* p) { return __bfloat162float(*p); }

__device__ __forceinline__ void stsm4(uint32_t addr, uint32_t a, uint32_t b, uint32_t c, uint32_t d) {
  asm volatile("stmatrix.sync.aligned.m8n8.x4.shared.b16 [%0], {%1, %2, %3, %4};" ::"r"(addr), "r"(a), "r"(b), "r"(c), "r"(d) : "memory");
}
__device__ __forceinline__ void stsm2(uint32_t addr, uint32_t a, uint32_t b) {
  asm volatile("stmatrix.sync.aligned.m8n8.x2.shared.b16 [%0], {%1, %2};" ::"r"(addr), "r"(a), "r"(b) : "memory");
}
__device__ __forceinline__ void stsm4t(uint32_t addr, uint32_t a, uint32_t b, uint32_t c, uint32_t d) {
  asm volatile("stmatrix.sync.aligned.m8n8.x4.trans.shared.b16 [%0], {%1, %2, %3, %4};" ::"r"(addr), "r"(a), "r"(b), "r"(c), "r"(d) : "memory");
}
__device__ __forceinline__ void ldsm4(uint32_t addr, uint32_t& a, uint32_t& b, uint32_t& c, uint32_t& d) {
  asm volatile("ldmatrix.sync.aligned.m8n8.x4.shared.b16 {%0, %1, %2, %3}, [%4];" : "=r"(a), "=r"(b), "=r"(c), "=r"(d) : "r"(addr) : "memory");
}
__device__ __forceinline__ void ldsm4t(uint32_t addr, uint32_t& a, uint32_t& b, uint32_t& c, uint32_t& d) {
  asm volatile("ldmatrix.sync.aligned.m8n8.x4.trans.shared.b16 {%0, %1, %2, %3}, [%4];" : "=r"(a), "=r"(b), "=r"(c), "=r"(d) : "r"(addr) : "memory");
}
__device__ __forceinline__ uint32_t lds32(uint32_t addr) {
  uint32_t v;
  asm volatile("ld.shared.u32 %0, [%1];" : "=r"(v) : "r"(addr) : "memory");
  return v;
}
__device__ __forceinline__ uint32_t lds16(uint32_t addr) {
  uint16_t v;
  asm volatile("ld.shared.u16 %0, [%1];" : "=h"(v) : "r"(addr) : "memory");
  return v;
}
__device__ __forceinline__ uint4 lds128(uint32_t addr) {
  uint4 v;
  asm volatile("ld.shared.v4.u32 {%0, %1, %2, %3}, [%4];" : "=r"(v.x), "=r"(v.y), "=r"(v.z), "=r"(v.w) : "r"(addr) : "memory");
  return v;
}
__device__ __forceinline__ uint2 lds64(uint32_t addr) {
  uint2 v;
  asm volatile("ld.shared.v2.u32 {%0, %1}, [%2];" : "=r"(v.x), "=r"(v.y) : "r"(addr) : "memory");
  return v;
}
__device__ __forceinline__ void sts32(uint32_t addr, uint32_t v) { asm volatile("st.shared.u32 [%0], %1;" ::"r"(addr), "r"(v) : "memory"); }
__device__ __forceinline__ void sts16(uint32_t addr, uint32_t v) { asm volatile("st.shared.u16 [%0], %1;" ::"r"(addr), "h"((uint16_t)v) : "memory"); }
__device__ __forceinline__ void sts128(uint32_t addr, uint32_t a, uint32_t b, uint32_t c, uint32_t d) {
  asm volatile("st.shared.v4.u32 [%0], {%1, %2, %3, %4};" ::"r"(addr), "r"(a), "r"(b), "r"(c), "r"(d) : "memory");
}
__device__ __forceinline__ void mma16816(float (&d)[4], uint32_t a0, uint32_t a1, uint32_t a2, uint32_t a3, uint32_t b0, uint32_t b1) {
  asm volatile("mma.sync.aligned.m16n8k16.row.col.f32.bf16.bf16.f32 {%0, %1, %2, %3}, {%4, %5, %6, %7}, {%8, %9}, {%0, %1, %2, %3};"
               : "+f"(d[0]), "+f"(d[1]), "+f"(d[2]), "+f"(d[3]) : "r"(a0), "r"(a1), "r"(a2), "r"(a3), "r"(b0), "r"(b1));
}

struct Cx { float re, im; };
__device__ __forceinline__ Cx cmul(Cx a, Cx b) {
  Cx r;
  r.re = fmaf(a.re, b.re, -(a.im * b.im));
  r.im = fmaf(a.re, b.im, a.im * b.re);
  return r;
}
__device__ __forceinline__ Cx cexp_boot(float a2, float tr, float e) {
  float mag = exp2f(a2 * e);
  float t = tr * e;
  t -= rintf(t);
  float s, c;
  s = __sinf(t * 6.283185307179586f);
  c = __cosf(t * 6.283185307179586f);
  Cx r; r.re = mag * c; r.im = mag * s;
  return r;
}

#define TSTAMP(i)

struct Ptrs {
  const __nv_bfloat16 *u, *logA, *Aim, *Cre, *Cim, *logdt, *Dskip, *gatew;
};

template <int G>
__device__ __forceinline__ void conv_mma(float (&acc)[16], const uint32_t (&w)[9], uint64_t descB, int first) {
  constexpr uint64_t KSTEP = (2 * PL_STRIDE) >> 4;
#pragma unroll
  for (int kk = 0; kk < 4; kk++) {
    const int sc = (first && kk == 0) ? 0 : 1;
    if (G == 0) wgmma_rs_n32(acc, w[2 * kk + 1], w[2 * kk], w[2 * kk + 2], w[2 * kk + 1], descB + kk * KSTEP, sc);
    if (G == 1) wgmma_rs_n24(acc, w[2 * kk + 1], w[2 * kk], w[2 * kk + 2], w[2 * kk + 1], descB + kk * KSTEP, 1);
    if (G == 2) wgmma_rs_n16(acc, w[2 * kk + 1], w[2 * kk], w[2 * kk + 2], w[2 * kk + 1], descB + kk * KSTEP, 1);
    if (G == 3) wgmma_rs_n8(acc, w[2 * kk + 1], w[2 * kk], w[2 * kk + 2], w[2 * kk + 1], descB + kk * KSTEP, 1);
  }
}
__device__ __forceinline__ void conv_ldA(uint32_t (&w)[9], uint32_t qaddr) {
#pragma unroll
  for (int i = 0; i < 9; i++) w[i] = lds32(qaddr - 32 * i);
}
template <int G>
__device__ __forceinline__ void conv_group(float (&acc)[16], uint32_t (&wa)[9], uint32_t (&wb)[9], uint32_t qaddr, uint32_t plbase) {
#pragma unroll
  for (int jj = 0; jj < 8; jj += 2) {
    const int j = 8 * G + jj;
    conv_ldA(wb, qaddr + (j + 1) * 256);
    wg_fence();
    conv_mma<G>(acc, wa, mkdesc(plbase + j * 16, PL_STRIDE, 128, 0), j == 0);
    wg_commit();
    wg_wait<1>();
    wg_fence();
    conv_mma<G>(acc, wb, mkdesc(plbase + (j + 1) * 16, PL_STRIDE, 128, 0), 0);
    wg_commit();
    wg_wait<1>();
    if (j + 2 < 32) conv_ldA(wa, qaddr + (j + 2) * 256);
  }
  wg_wait<0>();
  reg_fence(acc);
}

__global__ void __cluster_dims__(2, 1, 1) __launch_bounds__(NTHREADS, 1)
fused_kernel(const __grid_constant__ CUtensorMap tm_x, const __grid_constant__ CUtensorMap tm_w1,
             const __grid_constant__ CUtensorMap tm_hst, const __grid_constant__ CUtensorMap tm_hld,
             const __grid_constant__ CUtensorMap tm_w2, const __grid_constant__ CUtensorMap tm_aT,
             const __grid_constant__ CUtensorMap tm_out, const Ptrs P) {
  extern __shared__ uint8_t smem_raw[];
  const uint32_t sb = (smem_u32(smem_raw) + 1023u) & ~1023u;
  const uint32_t bar0 = sb + OFF_BAR;
  auto BAR = [&](int i) { return bar0 + 8 * i; };
  const int tid = threadIdx.x, warp = __shfl_sync(0xffffffffu, tid >> 5, 0), lane = tid & 31;
  const int cta = blockIdx.x, rank = cta & 1, cl = cta >> 1;
  const int i1 = 2 * (cl >> 3) + rank, j1 = cl & 7;
  const int i2 = cl >> 2, n2 = 2 * (cl & 3) + rank;

  if (tid == 256) {
    for (int s = 0; s < S1; s++) { mbar_init(BAR(BAR_FULL1 + s), 1); mbar_init(BAR(BAR_EMPTY1 + s), 16); }
    for (int s = 0; s < S2; s++) { mbar_init(BAR(BAR_FULL2 + s), 1); mbar_init(BAR(BAR_EMPTY2 + s), 16); }
    mbar_init(BAR(BAR_RINGFREE), 4);
    mbar_init(BAR(BAR_SLAB), 1);
    mbar_init(BAR(BAR_UFULL), 1);
    for (int c = 0; c < 5; c++) mbar_init(BAR(BAR_QREADY + c), 1);
    mbar_init(BAR(BAR_CONVDONE), 2);
    mbar_init(BAR(BAR_AFULL), 1);
    asm volatile("fence.mbarrier_init.release.cluster;" ::: "memory");
  }
  __syncthreads();
  asm volatile("barrier.cluster.arrive.release.aligned;\nbarrier.cluster.wait.acquire.aligned;" ::: "memory");

  if (warp >= 8) {
    asm volatile("setmaxnreg.dec.sync.aligned.u32 88;");
    const unsigned tag = *(volatile unsigned*)&g_epoch + 1u;
    if (warp == 8) {
      if (lane == 0) {
        TSTAMP(0);
        for (int ks = 0; ks < NK1; ks++) {
          const int s = ks % S1;
          if (ks >= S1) mbar_wait(BAR(BAR_EMPTY1 + s), ((ks / S1) & 1) ^ 1);
          const uint32_t st = sb + OFF_RING + s * ST1_BYTES, fb = BAR(BAR_FULL1 + s);
          mbar_expect_tx(fb, ST1_BYTES);
          tma_ld2(st, &tm_x, fb, ks * 64, i1 * 128);
          const int b0 = rank ? 4 : 0, b1 = rank ? 7 : 4;
          for (int b = b0; b < b1; b++) tma_ld2_mc(st + A1_BYTES + b * B1_BLK, &tm_w1, fb, j1 * BN1 + b * 32, ks * 64);
        }
        TSTAMP(1);
      }
      __syncwarp();
      mbar_wait(BAR(BAR_RINGFREE), 0);
      if (lane < 8) wait_flag(&g_flag_h[(2 * (8 * (i2 >> 1) + lane) + (i2 & 1)) * 2 + rank], tag);
      __syncwarp();
      if (lane == 0) {
        fence_async();
        TSTAMP(2);
        for (int ks = 0; ks < NK2; ks++) {
          const int s = ks % S2;
          if (ks >= S2) mbar_wait(BAR(BAR_EMPTY2 + s), ((ks / S2) & 1) ^ 1);
          const uint32_t st = sb + OFF_RING + s * ST2_BYTES, fb = BAR(BAR_FULL2 + s);
          mbar_expect_tx(fb, ST2_BYTES);
          tma_ld3(st + A2_BYTES, &tm_w2, fb, 0, ks * 64, n2 * 5);
          tma_ld2_mc(st + rank * 8192, &tm_hld, fb, ks * 64, i2 * 128 + rank * 64);
        }
        TSTAMP(3);
      }
    } else if (warp < 14) {
      const int ch = warp - 9, d = cta * 5 + ch;
      const uint32_t kg = sb + OFF_KG + ch * KG_BYTES;
      const float dt = bf16r(expf(ldbf(P.logdt + d)));
      float acc[5][4];
#pragma unroll
      for (int t = 0; t < 5; t++) { acc[t][0] = acc[t][1] = acc[t][2] = acc[t][3] = 0.f; }
      float k2048 = 0.f;
      const uint32_t lmA = kg + ((lane & 7) + 8 * ((lane >> 3) & 1)) * KG_PITCH + 16 * (lane >> 4);
      const uint32_t lmB = ((lane & 7) + 8 * (lane >> 4)) * KG_PITCH + 16 * ((lane >> 3) & 1);
      const uint32_t buf0 = kg, buf1 = kg + 16 * KG_PITCH;
#pragma unroll 1
      for (int q = 0; q < 4; q++) {
        const int n = d * NMODE + q * 32 + lane;
        const float are = -bf16r(expf(ldbf(P.logA + n)));
        const float lr = are * dt, li = ldbf(P.Aim + n) * dt;
        const Cx C = {ldbf(P.Cre + n), ldbf(P.Cim + n)};
        const float a2 = lr * 1.4426950408889634f, tr = li * 0.15915494309189535f;
        const Cx w1 = cexp_boot(a2, tr, 1.f), w128 = cexp_boot(a2, tr, 128.f);
        Cx w8c = cexp_boot(a2, tr, 8.f);
        w8c.im = -w8c.im;
        Cx y = {1.f, 0.f};
#pragma unroll
        for (int i = 0; i < 16; i++) {
          sts32(buf0 + i * KG_PITCH + lane * 4, pack_bf16(y.re, y.im));
          if (i < 15) y = cmul(y, w8c);
        }
        Cx x[8];
        x[0] = C;
#pragma unroll
        for (int b = 1; b < 8; b++) x[b] = cmul(x[b - 1], w1);
#pragma unroll
        for (int b = 0; b < 8; b++) sts32(buf1 + b * KG_PITCH + lane * 4, pack_bf16(x[b].re, x[b].im));
#pragma unroll
        for (int b = 0; b < 8; b++) {
          x[b] = cmul(x[b], w128);
          sts32(buf1 + (8 + b) * KG_PITCH + lane * 4, pack_bf16(x[b].re, x[b].im));
        }
        __syncwarp();
        uint32_t af[4][4];
#pragma unroll
        for (int s = 0; s < 4; s++) ldsm4(lmA + 32 * s, af[s][0], af[s][1], af[s][2], af[s][3]);
#pragma unroll
        for (int s = 0; s < 4; s++) {
          uint32_t b0, b1, b2, b3;
          ldsm4(buf1 + lmB + 32 * s, b0, b1, b2, b3);
          mma16816(acc[0], af[s][0], af[s][1], af[s][2], af[s][3], b0, b1);
          mma16816(acc[1], af[s][0], af[s][1], af[s][2], af[s][3], b2, b3);
        }
        __syncwarp();
#pragma unroll
        for (int a = 0; a < 2; a++) {
#pragma unroll
          for (int b = 0; b < 4; b++) {
            x[2 * b] = cmul(x[2 * b], w128);
            sts32(buf0 + (4 * a + b) * KG_PITCH + lane * 4, pack_bf16(x[2 * b].re, x[2 * b].im));
          }
        }
#pragma unroll
        for (int a = 0; a < 4; a++) {
#pragma unroll
          for (int b = 0; b < 2; b++) {
            x[4 * b] = cmul(x[4 * b], w128);
            sts32(buf0 + (8 + 2 * a + b) * KG_PITCH + lane * 4, pack_bf16(x[4 * b].re, x[4 * b].im));
          }
        }
#pragma unroll
        for (int a = 0; a < 8; a++) {
          x[0] = cmul(x[0], w128);
          sts32(buf1 + a * KG_PITCH + lane * 4, pack_bf16(x[0].re, x[0].im));
        }
        k2048 += fmaf(x[0].re, w128.re, -(x[0].im * w128.im));
        __syncwarp();
#pragma unroll
        for (int s = 0; s < 4; s++) {
          uint32_t b0, b1, b2, b3;
          ldsm4(buf0 + lmB + 32 * s, b0, b1, b2, b3);
          mma16816(acc[2], af[s][0], af[s][1], af[s][2], af[s][3], b0, b1);
          mma16816(acc[3], af[s][0], af[s][1], af[s][2], af[s][3], b2, b3);
          ldsm4(buf1 + lmB + 32 * s, b0, b1, b2, b3);
          mma16816(acc[4], af[s][0], af[s][1], af[s][2], af[s][3], b0, b1);
        }
        __syncwarp();
      }
#pragma unroll
      for (int o = 16; o; o >>= 1) k2048 += __shfl_xor_sync(0xffffffffu, k2048, o);
      const float sc = 2.f * dt;
      {
        const int g = lane >> 2, c = lane & 3;
#pragma unroll
        for (int h = 0; h < 2; h++) {
          const int i = g + 8 * h;
          sts32(kg + (8 * i + 2 * c) * 2, pack_bf16(sc * acc[0][2 * h], sc * acc[0][2 * h + 1]));
          sts32(kg + (128 + 8 * i + 2 * c) * 2, pack_bf16(sc * acc[1][2 * h], sc * acc[1][2 * h + 1]));
          sts32(kg + (256 + 4 * i + 64 * (c >> 1) + 2 * (c & 1)) * 2, pack_bf16(sc * acc[2][2 * h], sc * acc[2][2 * h + 1]));
          sts32(kg + (384 + 2 * i + 32 * c) * 2, pack_bf16(sc * acc[3][2 * h], sc * acc[3][2 * h + 1]));
          const uint32_t p4 = pack_bf16(sc * acc[4][2 * h], sc * acc[4][2 * h + 1]);
          sts16(kg + (512 + i + 32 * c) * 2, p4 & 0xffffu);
          sts16(kg + (512 + i + 32 * c + 16) * 2, p4 >> 16);
        }
        if (lane == 0) sts16(kg + 640 * 2, pack_bf16(sc * k2048, 0.f) & 0xffffu);
      }
      __syncwarp();
      {
        const uint32_t q = sb + OFF_Q + ch * Q_BYTES + 64 * 4;
        sts32(q - 256 + lane * 4, 0u);
        sts32(q - 128 + lane * 4, 0u);
        {
          const uint4 w = lds128(kg + lane * 16);
          const uint32_t pv = lane ? (lds16(kg + lane * 16 - 2) << 16) : 0u;
          sts128(q + lane * 32, __byte_perm(w.x, pv, 0x7610), __byte_perm(w.x, w.x, 0x1032), __byte_perm(w.y, w.x, 0x7610), __byte_perm(w.y, w.y, 0x1032));
          sts128(q + lane * 32 + 16, __byte_perm(w.z, w.y, 0x7610), __byte_perm(w.z, w.z, 0x1032), __byte_perm(w.w, w.z, 0x7610), __byte_perm(w.w, w.w, 0x1032));
        }
        {
          const uint2 w = lds64(kg + (256 + 4 * lane) * 2);
          const uint32_t v4 = lds16(kg + (256 + 4 * lane + 4) * 2);
          const uint32_t pv = lane ? (w.x & 0xffffu) : lds16(kg + 255 * 2);
          const uint32_t v0 = w.x & 0xffffu, v1 = w.x >> 16, v2 = w.y & 0xffffu, v3 = w.y >> 16;
          const uint32_t a = q + (256 + 8 * lane) * 4;
          sts128(a, v0 | (pv << 16), v0 | (v0 << 16), v1 | (v0 << 16), v2 | (v1 << 16));
          sts128(a + 16, v2 | (v2 << 16), v2 | (v2 << 16), v3 | (v2 << 16), v4 | (v3 << 16));
        }
#pragma unroll
        for (int t = 0; t < 2; t++) {
          const int m = lane + 32 * t;
          const uint32_t w = lds32(kg + (384 + 2 * m) * 2);
          const uint32_t A = w & 0xffffu, B = w >> 16, Cc = lds16(kg + (384 + 2 * m + 2) * 2);
          const uint32_t AA = A | (A << 16), BB = B | (B << 16);
          const uint32_t a = q + (512 + 8 * m) * 4;
          sts128(a, AA, AA, AA, B | (A << 16));
          sts128(a + 16, BB, BB, Cc | (B << 16), Cc | (Cc << 16));
        }
#pragma unroll
        for (int t = 0; t < 4; t++) {
          const int m = lane + 32 * t;
          const uint32_t A = lds16(kg + (512 + m) * 2), B = lds16(kg + (513 + m) * 2);
          const uint32_t AA = A | (A << 16), BB = B | (B << 16), BA = B | (A << 16);
          const uint32_t a = q + (1024 + 8 * m) * 4;
          const bool odd = m & 1;
          sts128(a, AA, AA, AA, AA);
          sts128(a + 16, odd ? BA : AA, odd ? BB : BA, BB, BB);
        }
      }
      __syncwarp();
      if (lane == 0) mbar_arrive(BAR(BAR_QREADY + ch));
      TSTAMP(8 + ch);
    } else if (warp == 14) {
      const int sp = cta >> 3, kap = cta & 7;
      const uint32_t slab = sb + OFF_PL;
      if (lane == 0) mbar_expect_tx(BAR(BAR_SLAB), 16 * D_ * 2);
      __syncwarp();
      if (lane < 16) {
        const int t = 64 * (2 * sp + 1 - (lane >> 3)) + 8 * kap + (lane & 7);
        bulk_ld(slab + lane * SLAB_PITCH, P.u + (size_t)t * D_, D_ * 2, BAR(BAR_SLAB));
      }
      uint32_t gw[10];
#pragma unroll
      for (int i = 0; i < 10; i++) gw[i] = ((const uint32_t*)P.gatew)[lane + 32 * i];
      mbar_wait(BAR(BAR_SLAB), 0);
      {
        const int mi = lane >> 3, i = lane & 7;
        const int row = (i >> 1) * 4 + (i & 1) + 2 * (mi & 1);
        const uint32_t la = slab + row * SLAB_PITCH + (mi >> 1) * 16;
        const int g = lane >> 2, c = lane & 3;
        uint8_t* dst = (uint8_t*)g_up + (size_t)g * 4096 + kap * 512 + (15 - sp) * 32 + c * 8;
#pragma unroll 4
        for (int it = 0; it < 40; it++) {
          const int d0 = it * 16;
          uint32_t r0, r1, r2, r3;
          ldsm4t(la + d0 * 2, r0, r1, r2, r3);
          *(uint2*)(dst + (size_t)d0 * 4096) = make_uint2(r0, r1);
          *(uint2*)(dst + (size_t)(d0 + 8) * 4096) = make_uint2(r2, r3);
        }
      }
#pragma unroll 2
      for (int row = 0; row < 16; row++) {
        float s = 0.f;
#pragma unroll
        for (int i = 0; i < 10; i++) {
          const uint32_t p = bmul2(lds32(slab + row * SLAB_PITCH + (lane + 32 * i) * 4), gw[i]);
          s += bf_lo(p);
          s += bf_hi(p);
        }
#pragma unroll
        for (int o = 16; o; o >>= 1) s += __shfl_xor_sync(0xffffffffu, s, o);
        if (lane == 0) {
          const float z = bf16r(s);
          g_gate[64 * (2 * sp + 1 - (row >> 3)) + 8 * kap + (row & 7)] = bf16r(1.f / (1.f + expf(-z)));
        }
      }
      __threadfence();
      __syncwarp();
      if (lane == 0) st_release(&g_flag_u[cta], tag);
      TSTAMP(4);
#pragma unroll
      for (int i = 0; i < 4; i++) wait_flag(&g_flag_u[32 * i + lane], tag);
      __syncwarp();
      const uint32_t pl = sb + OFF_PL;
      for (int i = lane; i < 5 * 8 * 9; i += 32) {
        const int p = i / 9, r = i % 9;
        sts128(pl + p * PL_STRIDE + (32 + r) * 16, 0u, 0u, 0u, 0u);
      }
      fence_async();
      __syncwarp();
      if (lane == 0) mbar_expect_tx(BAR(BAR_UFULL), 5 * 4096);
      __syncwarp();
      for (int p = lane; p < 40; p += 32)
        bulk_ld(pl + p * PL_STRIDE, (const uint8_t*)g_up + (size_t)(cta * 5) * 4096 + p * 512, 512, BAR(BAR_UFULL));
      TSTAMP(6);
      mbar_wait(BAR(BAR_CONVDONE), 0);
      wait_flag(&g_flag_a[n2 * 32 + lane], tag);
      __syncwarp();
      if (lane == 0) {
        fence_async();
        mbar_expect_tx(BAR(BAR_AFULL), 2 * 80 * 128);
        tma_ld2(sb + OFF_Q, &tm_aT, BAR(BAR_AFULL), i2 * 128, n2 * 80);
        tma_ld2(sb + OFF_Q + 80 * 128, &tm_aT, BAR(BAR_AFULL), i2 * 128 + 64, n2 * 80);
        TSTAMP(7);
      }
    }
  } else {
    asm volatile("setmaxnreg.inc.sync.aligned.u32 168;");
    const unsigned tag = *(volatile unsigned*)&g_epoch + 1u;
    const int wg = warp >> 2, w = warp & 3;
    const int r = lane >> 2, c = lane & 3;
    {
      float acc[108];
#pragma unroll 1
      for (int ks = 0; ks < NK1; ks++) {
        const int s = ks % S1;
        mbar_wait(BAR(BAR_FULL1 + s), (ks / S1) & 1);
        if (ks == 0) TSTAMP(16 + warp);
        const uint32_t st = sb + OFF_RING + s * ST1_BYTES;
        const uint64_t da = mkdesc(st + wg * 8192, 16, 1024, 1);
        const uint64_t db = mkdesc(st + A1_BYTES, B1_BLK, 512, 2);
        wg_fence();
#pragma unroll
        for (int kk = 0; kk < 4; kk++) {
          wgmma_ss_n128_tb(acc, da + 2 * kk, db + 64 * kk, (ks | kk) != 0);
          wgmma_ss_n88_tb(acc, da + 2 * kk, db + 64 * kk + ((4 * B1_BLK) >> 4), (ks | kk) != 0);
        }
        wg_commit();
        if (ks > 0) {
          wg_wait<1>();
          if (ks + S1 - 1 < NK1 && lane < 2) mbar_arrive_cta(BAR(BAR_EMPTY1 + (ks - 1) % S1), lane);
        }
      }
      wg_wait<0>();
      reg_fence(acc);
      TSTAMP(24 + warp);
      named_sync(1, 256);
      const uint32_t hst = sb + OFF_RING + wg * (64 * HST_PITCH);
      const uint32_t la = hst + (16 * w + 8 * ((lane >> 3) & 1) + (lane & 7)) * HST_PITCH + (lane >> 4) * 16;
#pragma unroll
      for (int i = 0; i < 26; i += 2)
        stsm4(la + i * 16, pack_bf16_relu(acc[4 * i], acc[4 * i + 1]), pack_bf16_relu(acc[4 * i + 2], acc[4 * i + 3]),
              pack_bf16_relu(acc[4 * i + 4], acc[4 * i + 5]), pack_bf16_relu(acc[4 * i + 6], acc[4 * i + 7]));
      stsm2(la + 26 * 16, pack_bf16_relu(acc[104], acc[105]), pack_bf16_relu(acc[106], acc[107]));
      fence_async_smem();
      named_sync(2 + wg, 128);
      if (w == 0 && lane == 0) {
        tma_st2(&tm_hst, hst, j1 * BN1, i1 * 128 + wg * 64);
        bulk_commit();
      }
    }
    mbar_wait(BAR(BAR_UFULL), 0);
#pragma unroll
    for (int ch = 0; ch < 5; ch++) mbar_wait(BAR(BAR_QREADY + ch), 0);
    if (w == 0 && lane == 0) {
      bulk_wait_read();
      mbar_arrive_cta(BAR(BAR_RINGFREE), 0);
      mbar_arrive_cta(BAR(BAR_RINGFREE), 1);
      bulk_wait_all();
      fence_async();
      __threadfence();
      st_release(&g_flag_h[cta * 2 + wg], tag);
    }
    __syncwarp();
    TSTAMP(32 + warp);
#pragma unroll 1
    for (int ch = wg; ch < 5; ch += 2) {
      const int d = cta * 5 + ch;
      const uint32_t plb = sb + OFF_PL + ch * PLCH_BYTES;
      const uint32_t qaddr = sb + OFF_Q + ch * Q_BYTES + (64 + 16 * w + (r - 2 * c) + 8) * 4;
      float acc[16];
      uint32_t wa[9], wb[9];
      conv_ldA(wa, qaddr);
      conv_group<0>(acc, wa, wb, qaddr, plb);
      conv_group<1>(acc, wa, wb, qaddr, plb);
      conv_group<2>(acc, wa, wb, qaddr, plb);
      conv_group<3>(acc, wa, wb, qaddr, plb);
      wg_wait<0>();
      reg_fence(acc);
      const uint32_t ys = sb + OFF_KG + wg * 4096;
      named_sync(2 + wg, 128);
      {
        const int mi = lane >> 3, jj = lane & 7, kp = 2 * w + (mi & 1);
#pragma unroll
        for (int i = 0; i < 4; i += 2) {
          const int a = 31 - 8 * (i + (mi >> 1)) - jj;
          stsm4t(ys + a * 128 + ((kp ^ (a & 7)) << 4), pack_bf16(acc[4 * i], acc[4 * i + 1]), pack_bf16(acc[4 * i + 2], acc[4 * i + 3]),
                 pack_bf16(acc[4 * i + 4], acc[4 * i + 5]), pack_bf16(acc[4 * i + 6], acc[4 * i + 7]));
        }
      }
      named_sync(2 + wg, 128);
      {
        const uint32_t dsk = (uint32_t)(*(const uint16_t*)(P.Dskip + d)) * 0x10001u;
        const int t128 = tid & 127, kp = t128 & 7;
#pragma unroll
        for (int it = 0; it < 2; it++) {
          const int a = (t128 >> 3) + 16 * it;
          const uint4 y = lds128(ys + a * 128 + ((kp ^ (a & 7)) << 4));
          const uint4 u = lds128(plb + kp * PL_STRIDE + (31 - a) * 16);
          uint4 o;
          o.x = badd2(y.x, bmul2(u.x, dsk)); o.y = badd2(y.y, bmul2(u.y, dsk));
          o.z = badd2(y.z, bmul2(u.z, dsk)); o.w = badd2(y.w, bmul2(u.w, dsk));
          *(uint4*)(g_aT + (size_t)d * L_ + 64 * a + 8 * kp) = o;
        }
      }
    }
    __threadfence();
    named_sync(2 + wg, 128);
    if (w == 0 && lane == 0) {
      st_release(&g_flag_a[cta * 2 + wg], tag);
      mbar_arrive(BAR(BAR_CONVDONE));
    }
    TSTAMP(40 + warp);
    {
      float acc[40];
#pragma unroll 1
      for (int ks = 0; ks < NK2; ks++) {
        const int s = ks % S2;
        mbar_wait(BAR(BAR_FULL2 + s), (ks / S2) & 1);
        const uint32_t st = sb + OFF_RING + s * ST2_BYTES;
        const uint64_t da = mkdesc(st + wg * 8192, 16, 1024, 1);
        const uint64_t db = mkdesc(st + A2_BYTES, B2_BLK, 256, 3);
        wg_fence();
#pragma unroll
        for (int kk = 0; kk < 4; kk++) wgmma_ss_n80_tb(acc, da + 2 * kk, db + 32 * kk, (ks | kk) != 0);
        wg_commit();
        if (ks > 0) {
          wg_wait<1>();
          if (ks + S2 - 1 < NK2 && lane < 2) mbar_arrive_cta(BAR(BAR_EMPTY2 + (ks - 1) % S2), lane);
        }
      }
      wg_wait<0>();
      reg_fence(acc);
      TSTAMP(48 + warp);
      const int t0 = i2 * 128 + wg * 64 + 16 * w;
      const float g0 = __ldcg(&g_gate[t0 + r]), g1 = __ldcg(&g_gate[t0 + r + 8]);
      const uint32_t gg[2] = {pack_bf16(g0, g0), pack_bf16(g1, g1)};
      const uint32_t og[2] = {pack_bf16(1.f - g0, 1.f - g0), pack_bf16(1.f - g1, 1.f - g1)};
      mbar_wait(BAR(BAR_AFULL), 0);
      const uint32_t at = sb + OFF_Q + wg * (80 * 128);
      const uint32_t os = sb + OFF_PL + wg * (64 * 160);
      const int mi = lane >> 3, jj = lane & 7, h = mi & 1;
#pragma unroll
      for (int i = 0; i < 10; i += 2) {
        const int dl = 8 * (i + (mi >> 1)) + jj;
        uint32_t a0, a1, a2, a3;
        ldsm4t(at + dl * 128 + (((2 * w + h) ^ jj) << 4), a0, a1, a2, a3);
        const uint32_t o0 = badd2(bmul2(gg[0], a0), bmul2(og[0], pack_bf16(acc[4 * i], acc[4 * i + 1])));
        const uint32_t o1 = badd2(bmul2(gg[1], a1), bmul2(og[1], pack_bf16(acc[4 * i + 2], acc[4 * i + 3])));
        const uint32_t o2 = badd2(bmul2(gg[0], a2), bmul2(og[0], pack_bf16(acc[4 * i + 4], acc[4 * i + 5])));
        const uint32_t o3 = badd2(bmul2(gg[1], a3), bmul2(og[1], pack_bf16(acc[4 * i + 6], acc[4 * i + 7])));
        stsm4(os + (16 * w + 8 * h + jj) * 160 + (i + (mi >> 1)) * 16, o0, o1, o2, o3);
      }
      fence_async_smem();
      named_sync(2 + wg, 128);
      if (w == 0 && lane == 0) {
        tma_st2(&tm_out, os, n2 * 80, i2 * 128 + wg * 64);
        bulk_commit();
        bulk_wait_read();
      }
      TSTAMP(56 + warp);
    }
  }
  __syncwarp();
  asm volatile("barrier.cluster.arrive.release.aligned;\nbarrier.cluster.wait.acquire.aligned;" ::: "memory");
  if (tid == 0) {
    const unsigned e = *(volatile unsigned*)&g_epoch;
    __threadfence();
    if (atomicAdd(&g_done, 1u) == NCTA - 1) {
      g_done = 0;
      __threadfence();
      *(volatile unsigned*)&g_epoch = e + 1u;
    }
  }
}

typedef CUresult (*EncodeFn)(CUtensorMap*, CUtensorMapDataType, cuuint32_t, void*, const cuuint64_t*, const cuuint64_t*,
                             const cuuint32_t*, const cuuint32_t*, CUtensorMapInterleave, CUtensorMapSwizzle,
                             CUtensorMapL2promotion, CUtensorMapFloatOOBfill);

void make_map(EncodeFn fn, CUtensorMap* m, const void* ptr, int rank, const cuuint64_t* dims, const cuuint64_t* strides,
              const cuuint32_t* box, CUtensorMapSwizzle swz) {
  cuuint32_t es[5] = {1, 1, 1, 1, 1};
  fn(m, CU_TENSOR_MAP_DATA_TYPE_BFLOAT16, rank, const_cast<void*>(ptr), dims, strides, box, es, CU_TENSOR_MAP_INTERLEAVE_NONE,
     swz, CU_TENSOR_MAP_L2_PROMOTION_L2_128B, CU_TENSOR_MAP_FLOAT_OOB_FILL_NONE);
}

}

extern "C" void kernel_launch(void* const* d_in, const int* in_sizes, int n_in, void* d_out, int out_size) {
  (void)in_sizes; (void)n_in; (void)out_size;
  static EncodeFn enc = nullptr;
  static void *p_h = nullptr, *p_aT = nullptr;
  if (!enc) {
    void* f = nullptr;
    cudaDriverEntryPointQueryResult qr;
    cudaGetDriverEntryPoint("cuTensorMapEncodeTiled", &f, cudaEnableDefault, &qr);
    enc = (EncodeFn)f;
    cudaGetSymbolAddress(&p_h, g_h);
    cudaGetSymbolAddress(&p_aT, g_aT);
    cudaFuncSetAttribute(fused_kernel, cudaFuncAttributeMaxDynamicSharedMemorySize, SMEM_BYTES);
  }
  const __nv_bfloat16* u = (const __nv_bfloat16*)d_in[0];
  const __nv_bfloat16* w1 = (const __nv_bfloat16*)d_in[8];
  const __nv_bfloat16* w2 = (const __nv_bfloat16*)d_in[9];
  CUtensorMap tm_x, tm_w1, tm_hst, tm_hld, tm_w2, tm_aT, tm_out;
  {
    cuuint64_t dims[2] = {D_, L_}, st[1] = {D_ * 2};
    cuuint32_t box[2] = {64, 128};
    make_map(enc, &tm_x, u, 2, dims, st, box, CU_TENSOR_MAP_SWIZZLE_128B);
    cuuint32_t boxo[2] = {80, 64};
    make_map(enc, &tm_out, d_out, 2, dims, st, boxo, CU_TENSOR_MAP_SWIZZLE_NONE);
  }
  {
    cuuint64_t dims[2] = {F_, D_}, st[1] = {F_ * 2};
    cuuint32_t box[2] = {32, 64};
    make_map(enc, &tm_w1, w1, 2, dims, st, box, CU_TENSOR_MAP_SWIZZLE_64B);
  }
  {
    cuuint64_t dims[2] = {F_, L_}, st[1] = {F_ * 2};
    cuuint32_t boxs[2] = {BN1, 64}, boxl[2] = {64, 64};
    make_map(enc, &tm_hst, p_h, 2, dims, st, boxs, CU_TENSOR_MAP_SWIZZLE_NONE);
    make_map(enc, &tm_hld, p_h, 2, dims, st, boxl, CU_TENSOR_MAP_SWIZZLE_128B);
  }
  {
    cuuint64_t dims[3] = {16, F_, D_ / 16}, st[2] = {D_ * 2, 32};
    cuuint32_t box[3] = {16, 64, 5};
    make_map(enc, &tm_w2, w2, 3, dims, st, box, CU_TENSOR_MAP_SWIZZLE_32B);
  }
  {
    cuuint64_t dims[2] = {L_, D_}, st[1] = {L_ * 2};
    cuuint32_t box[2] = {64, 80};
    make_map(enc, &tm_aT, p_aT, 2, dims, st, box, CU_TENSOR_MAP_SWIZZLE_128B);
  }
  Ptrs P;
  P.u = u;
  P.logA = (const __nv_bfloat16*)d_in[1];
  P.Aim = (const __nv_bfloat16*)d_in[2];
  P.Cre = (const __nv_bfloat16*)d_in[3];
  P.Cim = (const __nv_bfloat16*)d_in[4];
  P.logdt = (const __nv_bfloat16*)d_in[5];
  P.Dskip = (const __nv_bfloat16*)d_in[6];
  P.gatew = (const __nv_bfloat16*)d_in[10];
  fused_kernel<<<NCTA, NTHREADS, SMEM_BYTES>>>(tm_x, tm_w1, tm_hst, tm_hld, tm_w2, tm_aT, tm_out, P);
}
```

```cpp
#include <cuda_runtime.h>
#include <cuda_bf16.h>
#include <cuda_fp16.h>
#include <cuda.h>
#include <stdint.h>

namespace {

constexpr int L_ = 2048, D_ = 640, F_ = 1728, NMODE = 128;
constexpr int NCTA = 128;
constexpr int NTHREADS = 512;

constexpr int BN1 = 224, S1 = 3, NK1 = D_ / 64;
constexpr int A1_BYTES = 128 * 128;
constexpr int SB1 = 6;
constexpr int B1_BLK = 32 * 64;
constexpr int B1_BYTES = 7 * B1_BLK;
constexpr int OFF_B1 = S1 * A1_BYTES;
constexpr int RING1_BYTES = OFF_B1 + SB1 * B1_BYTES;
constexpr int S2 = 5, NK2 = F_ / 64;
constexpr int A2_BYTES = 64 * 128;
constexpr int B2_BLK = 32 * 64;
constexpr int B2_HALF = 5 * B2_BLK;
constexpr int ST2_BYTES = A2_BYTES + 2 * B2_HALF;
constexpr int OFF_RING = 0;
constexpr int RING_BYTES = S2 * ST2_BYTES;
constexpr int HST_BYTES = 7 * 64 * 64;
constexpr int PL_STRIDE = 78 * 16;
constexpr int PLCH_BYTES = 4 * PL_STRIDE;
constexpr int OFF_PL = RING_BYTES;
constexpr int Q_PAD = 32;
constexpr int QE_OFF = (Q_PAD + 1088) * 4 + 256;
constexpr int QO_OFF = QE_OFF + 512;
constexpr int Q_BYTES = QO_OFF + 256;
constexpr int OFF_Q = OFF_PL + 5 * PLCH_BYTES;
constexpr int YS_BYTES = 32 * 64 * 4;
constexpr int OFF_YS = OFF_Q + 5 * Q_BYTES;
constexpr int WB_PLANE = 1088;
constexpr int WB_BYTES = 4608;
constexpr int OFF_WB = OFF_YS + 2 * YS_BYTES;
constexpr int OFF_HO = OFF_WB + 2 * WB_BYTES;
constexpr int OFF_BAR = OFF_HO + 4096;
constexpr int OFF_KB = OFF_Q;
constexpr int OFF_KC = RING1_BYTES;
constexpr int KC_BYTES = 1296;
static_assert(OFF_KB + 13 * 4096 <= OFF_BAR && OFF_KC + 5 * KC_BYTES <= RING_BYTES, "kgen");
static_assert(Q_BYTES % 128 == 0 && Q_BYTES >= 4096 + 1023 && 4 * WB_PLANE <= WB_BYTES, "tables");
constexpr int SMEM_BYTES = OFF_BAR + 512;
static_assert(SMEM_BYTES <= 232448, "smem");
static_assert(RING1_BYTES <= RING_BYTES, "ring");
static_assert(16 * 1280 <= 5 * PLCH_BYTES && 2 * 80 * 128 <= 5 * PLCH_BYTES, "slab / aT");
static_assert(OFF_PL % 1024 == 0 && OFF_Q % 128 == 0 && OFF_YS % 128 == 0 && OFF_WB % 128 == 0 && OFF_BAR % 8 == 0, "align");

enum {
  BAR_FULL1 = 0, BAR_EMPTY1 = BAR_FULL1 + S1, BAR_FULLB = BAR_EMPTY1 + S1, BAR_EMPTYB = BAR_FULLB + SB1, BAR_FULL2 = BAR_EMPTYB + SB1, BAR_EMPTY2 = BAR_FULL2 + S2,
  BAR_RINGFREE = BAR_EMPTY2 + S2, BAR_SLAB, BAR_UFULL, BAR_QREADY, BAR_CONVDONE = BAR_QREADY + 5, BAR_AFULL = BAR_CONVDONE + 2, BAR_HST, BAR_PART = BAR_HST + 2, BAR_SEEN = BAR_PART + 5, BAR_COUNT
};
static_assert(BAR_COUNT * 8 <= 512, "bars");

__device__ __align__(1024) __nv_bfloat16 g_h[L_ * F_];
__device__ __align__(1024) __nv_bfloat16 g_up[D_ * PLCH_BYTES / 2];
__device__ __align__(1024) __nv_bfloat16 g_aT[D_ * L_];
__device__ __align__(1024) float g_gate[L_];
constexpr int CNT_U = 0;
constexpr int CNT_G = 1;
constexpr int CNT_H = CNT_G + 32;
constexpr int CNT_A = CNT_H + 32;
constexpr int CNT_COUNT = CNT_A + 4;
__device__ unsigned g_cnt[CNT_COUNT * 32];
__device__ unsigned g_done;

constexpr unsigned WAIT_LIMIT = 100000000u;
__device__ __forceinline__ int fresh_tid() {
  int t;
  asm volatile("mov.u32 %0, %%tid.x;" : "=r"(t));
  return t;
}
__device__ __forceinline__ uint32_t smem_u32(const void* p) { return (uint32_t)__cvta_generic_to_shared(p); }
__device__ __forceinline__ void mbar_init(uint32_t bar, int cnt) {
  asm volatile("mbarrier.init.shared::cta.b64 [%0], %1;" ::"r"(bar), "r"(cnt) : "memory");
}
__device__ __forceinline__ void mbar_expect_tx(uint32_t bar, int bytes) {
  asm volatile("mbarrier.arrive.expect_tx.shared::cta.b64 _, [%0], %1;" ::"r"(bar), "r"(bytes) : "memory");
}
__device__ __forceinline__ void mbar_arrive(uint32_t bar) {
  asm volatile("mbarrier.arrive.shared::cta.b64 _, [%0];" ::"r"(bar) : "memory");
}
__device__ __forceinline__ void mbar_arrive_cta(uint32_t bar, uint32_t cta) {
  asm volatile("{\n.reg .b32 ra;\nmapa.shared::cluster.u32 ra, %0, %1;\n"
               "mbarrier.arrive.shared::cluster.b64 _, [ra];\n}\n" ::"r"(bar), "r"(cta) : "memory");
}
__device__ __forceinline__ bool mbar_try(uint32_t bar, int parity) {
  uint32_t ok;
  asm volatile("{\n.reg .pred p;\nmbarrier.try_wait.parity.shared::cta.b64 p, [%1], %2;\nselp.u32 %0, 1, 0, p;\n}\n"
               : "=r"(ok) : "r"(bar), "r"(parity) : "memory");
  return ok != 0;
}
__device__ __forceinline__ void mbar_wait(uint32_t bar, int parity) {
  if (mbar_try(bar, parity)) return;
  const unsigned t0 = (unsigned)clock();
  while (!mbar_try(bar, parity)) {
    if ((unsigned)clock() - t0 > WAIT_LIMIT) break;
  }
}
__device__ __forceinline__ unsigned ld_acquire(const unsigned* p) {
  unsigned v;
  asm volatile("ld.acquire.gpu.global.u32 %0, [%1];" : "=r"(v) : "l"(p) : "memory");
  return v;
}
__device__ __forceinline__ void st_release(unsigned* p, unsigned v) {
  asm volatile("st.release.gpu.global.u32 [%0], %1;" ::"l"(p), "r"(v) : "memory");
}
__device__ __forceinline__ unsigned ld_relaxed(const unsigned* p) {
  unsigned v;
  asm volatile("ld.relaxed.gpu.global.u32 %0, [%1];" : "=r"(v) : "l"(p) : "memory");
  return v;
}
__device__ __forceinline__ void cnt_arrive(int idx) {
  asm volatile("red.release.gpu.global.add.u32 [%0], 1;" ::"l"(&g_cnt[idx * 32]) : "memory");
}
__device__ __forceinline__ void cnt_arrive_after_bulk(int idx) {
  asm volatile("red.relaxed.gpu.global.add.u32 [%0], 1;" ::"l"(&g_cnt[idx * 32]) : "memory");
}
__device__ __forceinline__ void cnt_wait(int idx, unsigned target) {
  if (ld_relaxed(&g_cnt[idx * 32]) >= target) return;
  const unsigned t0 = (unsigned)clock();
  while (ld_relaxed(&g_cnt[idx * 32]) < target) {
    if ((unsigned)clock() - t0 > WAIT_LIMIT) break;
  }
}
__device__ __forceinline__ void fence_async() { asm volatile("fence.proxy.async.global;" ::: "memory"); }
__device__ __forceinline__ void fence_async_smem() { asm volatile("fence.proxy.async.shared::cta;" ::: "memory"); }
__device__ __forceinline__ void named_sync(int id, int n) { asm volatile("bar.sync %0, %1;" ::"r"(id), "r"(n) : "memory"); }

__device__ __forceinline__ void tma_ld2(uint32_t dst, const CUtensorMap* m, uint32_t bar, int c0, int c1) {
  asm volatile("cp.async.bulk.tensor.2d.shared::cluster.global.mbarrier::complete_tx::bytes [%0], [%1, {%3, %4}], [%2];"
               ::"r"(dst), "l"(m), "r"(bar), "r"(c0), "r"(c1) : "memory");
}
__device__ __forceinline__ void tma_ld2_mc(uint32_t dst, const CUtensorMap* m, uint32_t bar, int c0, int c1) {
  asm volatile("cp.async.bulk.tensor.2d.shared::cluster.global.mbarrier::complete_tx::bytes.multicast::cluster "
               "[%0], [%1, {%3, %4}], [%2], %5;"
               ::"r"(dst), "l"(m), "r"(bar), "r"(c0), "r"(c1), "h"((uint16_t)3) : "memory");
}
__device__ __forceinline__ void tma_ld3(uint32_t dst, const CUtensorMap* m, uint32_t bar, int c0, int c1, int c2) {
  asm volatile("cp.async.bulk.tensor.3d.shared::cluster.global.mbarrier::complete_tx::bytes [%0], [%1, {%3, %4, %5}], [%2];"
               ::"r"(dst), "l"(m), "r"(bar), "r"(c0), "r"(c1), "r"(c2) : "memory");
}
__device__ __forceinline__ void tma_ld3_mc(uint32_t dst, const CUtensorMap* m, uint32_t bar, int c0, int c1, int c2) {
  asm volatile("cp.async.bulk.tensor.3d.shared::cluster.global.mbarrier::complete_tx::bytes.multicast::cluster "
               "[%0], [%1, {%3, %4, %5}], [%2], %6;"
               ::"r"(dst), "l"(m), "r"(bar), "r"(c0), "r"(c1), "r"(c2), "h"((uint16_t)3) : "memory");
}
__device__ __forceinline__ void tma_ld4_mc(uint32_t dst, const CUtensorMap* m, uint32_t bar, int c0, int c1, int c2, int c3) {
  asm volatile("cp.async.bulk.tensor.4d.shared::cluster.global.mbarrier::complete_tx::bytes.multicast::cluster "
               "[%0], [%1, {%3, %4, %5, %6}], [%2], %7;"
               ::"r"(dst), "l"(m), "r"(bar), "r"(c0), "r"(c1), "r"(c2), "r"(c3), "h"((uint16_t)3) : "memory");
}
__device__ __forceinline__ void tma_ld4(uint32_t dst, const CUtensorMap* m, uint32_t bar, int c0, int c1, int c2, int c3) {
  asm volatile("cp.async.bulk.tensor.4d.shared::cluster.global.mbarrier::complete_tx::bytes [%0], [%1, {%3, %4, %5, %6}], [%2];"
               ::"r"(dst), "l"(m), "r"(bar), "r"(c0), "r"(c1), "r"(c2), "r"(c3) : "memory");
}
__device__ __forceinline__ void tma_st2(const CUtensorMap* m, uint32_t src, int c0, int c1) {
  asm volatile("cp.async.bulk.tensor.2d.global.shared::cta.bulk_group [%0, {%2, %3}], [%1];"
               ::"l"(m), "r"(src), "r"(c0), "r"(c1) : "memory");
}
__device__ __forceinline__ void tma_st3(const CUtensorMap* m, uint32_t src, int c0, int c1, int c2) {
  asm volatile("cp.async.bulk.tensor.3d.global.shared::cta.bulk_group [%0, {%2, %3, %4}], [%1];"
               ::"l"(m), "r"(src), "r"(c0), "r"(c1), "r"(c2) : "memory");
}
__device__ __forceinline__ void bulk_ld(uint32_t dst, const void* src, int bytes, uint32_t bar) {
  asm volatile("cp.async.bulk.shared::cluster.global.mbarrier::complete_tx::bytes [%0], [%1], %2, [%3];"
               ::"r"(dst), "l"(src), "r"(bytes), "r"(bar) : "memory");
}
__device__ __forceinline__ void l2_prefetch(const void* p, int bytes) {
  asm volatile("cp.async.bulk.prefetch.L2.global [%0], %1;" ::"l"(p), "r"(bytes) : "memory");
}
__device__ __forceinline__ void prefetch_tmap(const CUtensorMap* m) { asm volatile("prefetch.tensormap [%0];" ::"l"(m) : "memory"); }
__device__ __forceinline__ void cluster_wait() { asm volatile("barrier.cluster.wait.aligned;" ::: "memory"); }
__device__ __forceinline__ void bulk_commit() { asm volatile("cp.async.bulk.commit_group;" ::: "memory"); }
__device__ __forceinline__ void bulk_wait_read() { asm volatile("cp.async.bulk.wait_group.read 0;" ::: "memory"); }
__device__ __forceinline__ void bulk_wait_all() { asm volatile("cp.async.bulk.wait_group 0;" ::: "memory"); }

__device__ __forceinline__ void wg_fence() { asm volatile("wgmma.fence.sync.aligned;" ::: "memory"); }
__device__ __forceinline__ void wg_commit() { asm volatile("wgmma.commit_group.sync.aligned;" ::: "memory"); }
template <int N> __device__ __forceinline__ void wg_wait() { asm volatile("wgmma.wait_group.sync.aligned %0;" ::"n"(N) : "memory"); }
__device__ __forceinline__ uint64_t mkdesc(uint32_t addr, uint32_t lbo, uint32_t sbo, int swz) {
  return (uint64_t)((addr & 0x3FFFF) >> 4) | ((uint64_t)(lbo >> 4) << 16) | ((uint64_t)(sbo >> 4) << 32) | ((uint64_t)swz << 62);
}
template <int N> __device__ __forceinline__ void reg_fence(float (&d)[N]) {
#pragma unroll
  for (int i = 0; i < N; i++) asm volatile("" : "+f"(d[i])::"memory");
}

__device__ __forceinline__ void wgmma_rs_n128_tb(float (&d)[112], uint32_t a0, uint32_t a1, uint32_t a2, uint32_t a3, uint64_t db, int sc) {
  asm volatile("{\n.reg .pred p;\nsetp.ne.b32 p, %69, 0;\n"
    "wgmma.mma_async.sync.aligned.m64n128k16.f32.bf16.bf16 "
    "{%0, %1, %2, %3, %4, %5, %6, %7, %8, %9, %10, %11, %12, %13, %14, %15, %16, %17, %18, %19, %20, %21, %22, %23, %24, %25, %26, %27, %28, %29, %30, %31, %32, %33, %34, %35, %36, %37, %38, %39, %40, %41, %42, %43, %44, %45, %46, %47, %48, %49, %50, %51, %52, %53, %54, %55, %56, %57, %58, %59, %60, %61, %62, %63}, {%64, %65, %66, %67}, %68, p, 1, 1, 1;\n}\n"
    : "+f"(d[0]), "+f"(d[1]), "+f"(d[2]), "+f"(d[3]), "+f"(d[4]), "+f"(d[5]), "+f"(d[6]), "+f"(d[7]), "+f"(d[8]), "+f"(d[9]), "+f"(d[10]), "+f"(d[11]), "+f"(d[12]), "+f"(d[13]), "+f"(d[14]), "+f"(d[15]), "+f"(d[16]), "+f"(d[17]), "+f"(d[18]), "+f"(d[19]), "+f"(d[20]), "+f"(d[21]), "+f"(d[22]), "+f"(d[23]), "+f"(d[24]), "+f"(d[25]), "+f"(d[26]), "+f"(d[27]), "+f"(d[28]), "+f"(d[29]), "+f"(d[30]), "+f"(d[31]), "+f"(d[32]), "+f"(d[33]), "+f"(d[34]), "+f"(d[35]), "+f"(d[36]), "+f"(d[37]), "+f"(d[38]), "+f"(d[39]), "+f"(d[40]), "+f"(d[41]), "+f"(d[42]), "+f"(d[43]), "+f"(d[44]), "+f"(d[45]), "+f"(d[46]), "+f"(d[47]), "+f"(d[48]), "+f"(d[49]), "+f"(d[50]), "+f"(d[51]), "+f"(d[52]), "+f"(d[53]), "+f"(d[54]), "+f"(d[55]), "+f"(d[56]), "+f"(d[57]), "+f"(d[58]), "+f"(d[59]), "+f"(d[60]), "+f"(d[61]), "+f"(d[62]), "+f"(d[63])
    : "r"(a0), "r"(a1), "r"(a2), "r"(a3), "l"(db), "r"(sc));
}
__device__ __forceinline__ void wgmma_rs_n96_tb(float (&d)[112], uint32_t a0, uint32_t a1, uint32_t a2, uint32_t a3, uint64_t db, int sc) {
  asm volatile("{\n.reg .pred p;\nsetp.ne.b32 p, %53, 0;\n"
    "wgmma.mma_async.sync.aligned.m64n96k16.f32.bf16.bf16 "
    "{%0, %1, %2, %3, %4, %5, %6, %7, %8, %9, %10, %11, %12, %13, %14, %15, %16, %17, %18, %19, %20, %21, %22, %23, %24, %25, %26, %27, %28, %29, %30, %31, %32, %33, %34, %35, %36, %37, %38, %39, %40, %41, %42, %43, %44, %45, %46, %47}, {%48, %49, %50, %51}, %52, p, 1, 1, 1;\n}\n"
    : "+f"(d[64]), "+f"(d[65]), "+f"(d[66]), "+f"(d[67]), "+f"(d[68]), "+f"(d[69]), "+f"(d[70]), "+f"(d[71]), "+f"(d[72]), "+f"(d[73]), "+f"(d[74]), "+f"(d[75]), "+f"(d[76]), "+f"(d[77]), "+f"(d[78]), "+f"(d[79]), "+f"(d[80]), "+f"(d[81]), "+f"(d[82]), "+f"(d[83]), "+f"(d[84]), "+f"(d[85]), "+f"(d[86]), "+f"(d[87]), "+f"(d[88]), "+f"(d[89]), "+f"(d[90]), "+f"(d[91]), "+f"(d[92]), "+f"(d[93]), "+f"(d[94]), "+f"(d[95]), "+f"(d[96]), "+f"(d[97]), "+f"(d[98]), "+f"(d[99]), "+f"(d[100]), "+f"(d[101]), "+f"(d[102]), "+f"(d[103]), "+f"(d[104]), "+f"(d[105]), "+f"(d[106]), "+f"(d[107]), "+f"(d[108]), "+f"(d[109]), "+f"(d[110]), "+f"(d[111])
    : "r"(a0), "r"(a1), "r"(a2), "r"(a3), "l"(db), "r"(sc));
}
__device__ __forceinline__ void wgmma_ss_n160_tb(float (&d)[80], uint64_t da, uint64_t db, int sc) {
  asm volatile("{\n.reg .pred p;\nsetp.ne.b32 p, %82, 0;\n"
    "wgmma.mma_async.sync.aligned.m64n160k16.f32.bf16.bf16 "
    "{%0, %1, %2, %3, %4, %5, %6, %7, %8, %9, %10, %11, %12, %13, %14, %15, %16, %17, %18, %19, %20, %21, %22, %23, %24, %25, %26, %27, %28, %29, %30, %31, %32, %33, %34, %35, %36, %37, %38, %39, %40, %41, %42, %43, %44, %45, %46, %47, %48, %49, %50, %51, %52, %53, %54, %55, %56, %57, %58, %59, %60, %61, %62, %63, %64, %65, %66, %67, %68, %69, %70, %71, %72, %73, %74, %75, %76, %77, %78, %79}, "
    "%80, %81, p, 1, 1, 0, 1;\n}\n"
    : "+f"(d[0]), "+f"(d[1]), "+f"(d[2]), "+f"(d[3]), "+f"(d[4]), "+f"(d[5]), "+f"(d[6]), "+f"(d[7]), "+f"(d[8]), "+f"(d[9]), "+f"(d[10]), "+f"(d[11]), "+f"(d[12]), "+f"(d[13]), "+f"(d[14]), "+f"(d[15]), "+f"(d[16]), "+f"(d[17]), "+f"(d[18]), "+f"(d[19]), "+f"(d[20]), "+f"(d[21]), "+f"(d[22]), "+f"(d[23]), "+f"(d[24]), "+f"(d[25]), "+f"(d[26]), "+f"(d[27]), "+f"(d[28]), "+f"(d[29]), "+f"(d[30]), "+f"(d[31]), "+f"(d[32]), "+f"(d[33]), "+f"(d[34]), "+f"(d[35]), "+f"(d[36]), "+f"(d[37]), "+f"(d[38]), "+f"(d[39]), "+f"(d[40]), "+f"(d[41]), "+f"(d[42]), "+f"(d[43]), "+f"(d[44]), "+f"(d[45]), "+f"(d[46]), "+f"(d[47]), "+f"(d[48]), "+f"(d[49]), "+f"(d[50]), "+f"(d[51]), "+f"(d[52]), "+f"(d[53]), "+f"(d[54]), "+f"(d[55]), "+f"(d[56]), "+f"(d[57]), "+f"(d[58]), "+f"(d[59]), "+f"(d[60]), "+f"(d[61]), "+f"(d[62]), "+f"(d[63]), "+f"(d[64]), "+f"(d[65]), "+f"(d[66]), "+f"(d[67]), "+f"(d[68]), "+f"(d[69]), "+f"(d[70]), "+f"(d[71]), "+f"(d[72]), "+f"(d[73]), "+f"(d[74]), "+f"(d[75]), "+f"(d[76]), "+f"(d[77]), "+f"(d[78]), "+f"(d[79])
    : "l"(da), "l"(db), "r"(sc));
}
__device__ __forceinline__ void wgmma_rs_n64(float (&d)[32], uint32_t a0, uint32_t a1, uint32_t a2, uint32_t a3, uint64_t db, int sc) {
  asm volatile("{\n.reg .pred p;\nsetp.ne.b32 p, %37, 0;\n"
    "wgmma.mma_async.sync.aligned.m64n64k16.f32.bf16.bf16 "
    "{%0, %1, %2, %3, %4, %5, %6, %7, %8, %9, %10, %11, %12, %13, %14, %15, %16, %17, %18, %19, %20, %21, %22, %23, %24, %25, %26, %27, %28, %29, %30, %31}, {%32, %33, %34, %35}, %36, p, 1, 1, 0;\n}\n"
    : "+f"(d[0]), "+f"(d[1]), "+f"(d[2]), "+f"(d[3]), "+f"(d[4]), "+f"(d[5]), "+f"(d[6]), "+f"(d[7]), "+f"(d[8]), "+f"(d[9]), "+f"(d[10]), "+f"(d[11]), "+f"(d[12]), "+f"(d[13]), "+f"(d[14]), "+f"(d[15]), "+f"(d[16]), "+f"(d[17]), "+f"(d[18]), "+f"(d[19]), "+f"(d[20]), "+f"(d[21]), "+f"(d[22]), "+f"(d[23]), "+f"(d[24]), "+f"(d[25]), "+f"(d[26]), "+f"(d[27]), "+f"(d[28]), "+f"(d[29]), "+f"(d[30]), "+f"(d[31])
    : "r"(a0), "r"(a1), "r"(a2), "r"(a3), "l"(db), "r"(sc));
}
__device__ __forceinline__ void wgmma_rs_n56(float (&d)[32], uint32_t a0, uint32_t a1, uint32_t a2, uint32_t a3, uint64_t db, int sc) {
  asm volatile("{\n.reg .pred p;\nsetp.ne.b32 p, %33, 0;\n"
    "wgmma.mma_async.sync.aligned.m64n56k16.f32.bf16.bf16 "
    "{%0, %1, %2, %3, %4, %5, %6, %7, %8, %9, %10, %11, %12, %13, %14, %15, %16, %17, %18, %19, %20, %21, %22, %23, %24, %25, %26, %27}, {%28, %29, %30, %31}, %32, p, 1, 1, 0;\n}\n"
    : "+f"(d[0]), "+f"(d[1]), "+f"(d[2]), "+f"(d[3]), "+f"(d[4]), "+f"(d[5]), "+f"(d[6]), "+f"(d[7]), "+f"(d[8]), "+f"(d[9]), "+f"(d[10]), "+f"(d[11]), "+f"(d[12]), "+f"(d[13]), "+f"(d[14]), "+f"(d[15]), "+f"(d[16]), "+f"(d[17]), "+f"(d[18]), "+f"(d[19]), "+f"(d[20]), "+f"(d[21]), "+f"(d[22]), "+f"(d[23]), "+f"(d[24]), "+f"(d[25]), "+f"(d[26]), "+f"(d[27])
    : "r"(a0), "r"(a1), "r"(a2), "r"(a3), "l"(db), "r"(sc));
}
__device__ __forceinline__ void wgmma_rs_n48(float (&d)[32], uint32_t a0, uint32_t a1, uint32_t a2, uint32_t a3, uint64_t db, int sc) {
  asm volatile("{\n.reg .pred p;\nsetp.ne.b32 p, %29, 0;\n"
    "wgmma.mma_async.sync.aligned.m64n48k16.f32.bf16.bf16 "
    "{%0, %1, %2, %3, %4, %5, %6, %7, %8, %9, %10, %11, %12, %13, %14, %15, %16, %17, %18, %19, %20, %21, %22, %23}, {%24, %25, %26, %27}, %28, p, 1, 1, 0;\n}\n"
    : "+f"(d[0]), "+f"(d[1]), "+f"(d[2]), "+f"(d[3]), "+f"(d[4]), "+f"(d[5]), "+f"(d[6]), "+f"(d[7]), "+f"(d[8]), "+f"(d[9]), "+f"(d[10]), "+f"(d[11]), "+f"(d[12]), "+f"(d[13]), "+f"(d[14]), "+f"(d[15]), "+f"(d[16]), "+f"(d[17]), "+f"(d[18]), "+f"(d[19]), "+f"(d[20]), "+f"(d[21]), "+f"(d[22]), "+f"(d[23])
    : "r"(a0), "r"(a1), "r"(a2), "r"(a3), "l"(db), "r"(sc));
}
__device__ __forceinline__ void wgmma_rs_n40(float (&d)[32], uint32_t a0, uint32_t a1, uint32_t a2, uint32_t a3, uint64_t db, int sc) {
  asm volatile("{\n.reg .pred p;\nsetp.ne.b32 p, %25, 0;\n"
    "wgmma.mma_async.sync.aligned.m64n40k16.f32.bf16.bf16 "
    "{%0, %1, %2, %3, %4, %5, %6, %7, %8, %9, %10, %11, %12, %13, %14, %15, %16, %17, %18, %19}, {%20, %21, %22, %23}, %24, p, 1, 1, 0;\n}\n"
    : "+f"(d[0]), "+f"(d[1]), "+f"(d[2]), "+f"(d[3]), "+f"(d[4]), "+f"(d[5]), "+f"(d[6]), "+f"(d[7]), "+f"(d[8]), "+f"(d[9]), "+f"(d[10]), "+f"(d[11]), "+f"(d[12]), "+f"(d[13]), "+f"(d[14]), "+f"(d[15]), "+f"(d[16]), "+f"(d[17]), "+f"(d[18]), "+f"(d[19])
    : "r"(a0), "r"(a1), "r"(a2), "r"(a3), "l"(db), "r"(sc));
}
__device__ __forceinline__ void wgmma_rs_n32(float (&d)[32], uint32_t a0, uint32_t a1, uint32_t a2, uint32_t a3, uint64_t db, int sc) {
  asm volatile("{\n.reg .pred p;\nsetp.ne.b32 p, %21, 0;\n"
    "wgmma.mma_async.sync.aligned.m64n32k16.f32.bf16.bf16 "
    "{%0, %1, %2, %3, %4, %5, %6, %7, %8, %9, %10, %11, %12, %13, %14, %15}, {%16, %17, %18, %19}, %20, p, 1, 1, 0;\n}\n"
    : "+f"(d[0]), "+f"(d[1]), "+f"(d[2]), "+f"(d[3]), "+f"(d[4]), "+f"(d[5]), "+f"(d[6]), "+f"(d[7]), "+f"(d[8]), "+f"(d[9]), "+f"(d[10]), "+f"(d[11]), "+f"(d[12]), "+f"(d[13]), "+f"(d[14]), "+f"(d[15])
    : "r"(a0), "r"(a1), "r"(a2), "r"(a3), "l"(db), "r"(sc));
}
__device__ __forceinline__ void wgmma_rs_n24(float (&d)[32], uint32_t a0, uint32_t a1, uint32_t a2, uint32_t a3, uint64_t db, int sc) {
  asm volatile("{\n.reg .pred p;\nsetp.ne.b32 p, %17, 0;\n"
    "wgmma.mma_async.sync.aligned.m64n24k16.f32.bf16.bf16 "
    "{%0, %1, %2, %3, %4, %5, %6, %7, %8, %9, %10, %11}, {%12, %13, %14, %15}, %16, p, 1, 1, 0;\n}\n"
    : "+f"(d[0]), "+f"(d[1]), "+f"(d[2]), "+f"(d[3]), "+f"(d[4]), "+f"(d[5]), "+f"(d[6]), "+f"(d[7]), "+f"(d[8]), "+f"(d[9]), "+f"(d[10]), "+f"(d[11])
    : "r"(a0), "r"(a1), "r"(a2), "r"(a3), "l"(db), "r"(sc));
}
__device__ __forceinline__ void wgmma_rs_n16(float (&d)[32], uint32_t a0, uint32_t a1, uint32_t a2, uint32_t a3, uint64_t db, int sc) {
  asm volatile("{\n.reg .pred p;\nsetp.ne.b32 p, %13, 0;\n"
    "wgmma.mma_async.sync.aligned.m64n16k16.f32.bf16.bf16 "
    "{%0, %1, %2, %3, %4, %5, %6, %7}, {%8, %9, %10, %11}, %12, p, 1, 1, 0;\n}\n"
    : "+f"(d[0]), "+f"(d[1]), "+f"(d[2]), "+f"(d[3]), "+f"(d[4]), "+f"(d[5]), "+f"(d[6]), "+f"(d[7])
    : "r"(a0), "r"(a1), "r"(a2), "r"(a3), "l"(db), "r"(sc));
}
__device__ __forceinline__ void wgmma_rs_n8(float (&d)[32], uint32_t a0, uint32_t a1, uint32_t a2, uint32_t a3, uint64_t db, int sc) {
  asm volatile("{\n.reg .pred p;\nsetp.ne.b32 p, %9, 0;\n"
    "wgmma.mma_async.sync.aligned.m64n8k16.f32.bf16.bf16 "
    "{%0, %1, %2, %3}, {%4, %5, %6, %7}, %8, p, 1, 1, 0;\n}\n"
    : "+f"(d[0]), "+f"(d[1]), "+f"(d[2]), "+f"(d[3])
    : "r"(a0), "r"(a1), "r"(a2), "r"(a3), "l"(db), "r"(sc));
}
__device__ __forceinline__ void wgmma_rs_n16_tb(float (&d)[8], uint32_t a0, uint32_t a1, uint32_t a2, uint32_t a3, uint64_t db, int sc) {
  asm volatile("{\n.reg .pred p;\nsetp.ne.b32 p, %13, 0;\n"
    "wgmma.mma_async.sync.aligned.m64n16k16.f32.bf16.bf16 "
    "{%0, %1, %2, %3, %4, %5, %6, %7}, {%8, %9, %10, %11}, %12, p, 1, 1, 1;\n}\n"
    : "+f"(d[0]), "+f"(d[1]), "+f"(d[2]), "+f"(d[3]), "+f"(d[4]), "+f"(d[5]), "+f"(d[6]), "+f"(d[7])
    : "r"(a0), "r"(a1), "r"(a2), "r"(a3), "l"(db), "r"(sc));
}

__device__ __forceinline__ uint32_t pack_bf16(float lo, float hi) {
  uint32_t r;
  asm("cvt.rn.bf16x2.f32 %0, %1, %2;" : "=r"(r) : "f"(hi), "f"(lo));
  return r;
}
__device__ __forceinline__ uint32_t pack_bf16_relu(float lo, float hi) {
  uint32_t r;
  asm("cvt.rn.relu.bf16x2.f32 %0, %1, %2;" : "=r"(r) : "f"(hi), "f"(lo));
  return r;
}
__device__ __forceinline__ uint32_t bmul2(uint32_t a, uint32_t b) {
  uint32_t r;
  asm("mul.rn.bf16x2 %0, %1, %2;" : "=r"(r) : "r"(a), "r"(b));
  return r;
}
__device__ __forceinline__ uint32_t badd2(uint32_t a, uint32_t b) {
  uint32_t r;
  asm("add.rn.bf16x2 %0, %1, %2;" : "=r"(r) : "r"(a), "r"(b));
  return r;
}
__device__ __forceinline__ float bf_lo(uint32_t w) { return __uint_as_float(w << 16); }
__device__ __forceinline__ float bf_hi(uint32_t w) { return __uint_as_float(w & 0xffff0000u); }
__device__ __forceinline__ float bf16r(float x) { return __bfloat162float(__float2bfloat16_rn(x)); }
__device__ __forceinline__ uint2 ldg64_nc(const void* p) {
  uint2 v;
  asm volatile("ld.global.nc.v2.u32 {%0, %1}, [%2];" : "=r"(v.x), "=r"(v.y) : "l"(p));
  return v;
}
__device__ __forceinline__ uint32_t ldg16_nc(const void* p) {
  uint16_t v;
  asm volatile("ld.global.nc.u16 %0, [%1];" : "=h"(v) : "l"(p));
  return v;
}
__device__ __forceinline__ uint16_t ldu16(const __nv_bfloat16* p) { return __ldg((const unsigned short*)p); }
__device__ __forceinline__ float ldbf(const __nv_bfloat16* p) { return __bfloat162float(*p); }

__device__ __forceinline__ void stsm4(uint32_t addr, uint32_t a, uint32_t b, uint32_t c, uint32_t d) {
  asm volatile("stmatrix.sync.aligned.m8n8.x4.shared.b16 [%0], {%1, %2, %3, %4};" ::"r"(addr), "r"(a), "r"(b), "r"(c), "r"(d) : "memory");
}
__device__ __forceinline__ void stsm2(uint32_t addr, uint32_t a, uint32_t b) {
  asm volatile("stmatrix.sync.aligned.m8n8.x2.shared.b16 [%0], {%1, %2};" ::"r"(addr), "r"(a), "r"(b) : "memory");
}
__device__ __forceinline__ void stsm4t(uint32_t addr, uint32_t a, uint32_t b, uint32_t c, uint32_t d) {
  asm volatile("stmatrix.sync.aligned.m8n8.x4.trans.shared.b16 [%0], {%1, %2, %3, %4};" ::"r"(addr), "r"(a), "r"(b), "r"(c), "r"(d) : "memory");
}
__device__ __forceinline__ void ldsm4(uint32_t addr, uint32_t& a, uint32_t& b, uint32_t& c, uint32_t& d) {
  asm volatile("ldmatrix.sync.aligned.m8n8.x4.shared.b16 {%0, %1, %2, %3}, [%4];" : "=r"(a), "=r"(b), "=r"(c), "=r"(d) : "r"(addr) : "memory");
}
__device__ __forceinline__ void ldsm2(uint32_t addr, uint32_t& a, uint32_t& b) {
  asm volatile("ldmatrix.sync.aligned.m8n8.x2.shared.b16 {%0, %1}, [%2];" : "=r"(a), "=r"(b) : "r"(addr) : "memory");
}
__device__ __forceinline__ void ldsm4t(uint32_t addr, uint32_t& a, uint32_t& b, uint32_t& c, uint32_t& d) {
  asm volatile("ldmatrix.sync.aligned.m8n8.x4.trans.shared.b16 {%0, %1, %2, %3}, [%4];" : "=r"(a), "=r"(b), "=r"(c), "=r"(d) : "r"(addr) : "memory");
}
__device__ __forceinline__ uint32_t lds32(uint32_t addr) {
  uint32_t v;
  asm volatile("ld.shared.u32 %0, [%1];" : "=r"(v) : "r"(addr) : "memory");
  return v;
}
__device__ __forceinline__ uint32_t lds16(uint32_t addr) {
  uint16_t v;
  asm volatile("ld.shared.u16 %0, [%1];" : "=h"(v) : "r"(addr) : "memory");
  return v;
}
__device__ __forceinline__ uint4 lds128(uint32_t addr) {
  uint4 v;
  asm volatile("ld.shared.v4.u32 {%0, %1, %2, %3}, [%4];" : "=r"(v.x), "=r"(v.y), "=r"(v.z), "=r"(v.w) : "r"(addr) : "memory");
  return v;
}
__device__ __forceinline__ uint2 lds64(uint32_t addr) {
  uint2 v;
  asm volatile("ld.shared.v2.u32 {%0, %1}, [%2];" : "=r"(v.x), "=r"(v.y) : "r"(addr) : "memory");
  return v;
}
__device__ __forceinline__ void sts32(uint32_t addr, uint32_t v) { asm volatile("st.shared.u32 [%0], %1;" ::"r"(addr), "r"(v) : "memory"); }
__device__ __forceinline__ void sts16(uint32_t addr, uint32_t v) { asm volatile("st.shared.u16 [%0], %1;" ::"r"(addr), "h"((uint16_t)v) : "memory"); }
__device__ __forceinline__ void sts128(uint32_t addr, uint32_t a, uint32_t b, uint32_t c, uint32_t d) {
  asm volatile("st.shared.v4.u32 [%0], {%1, %2, %3, %4};" ::"r"(addr), "r"(a), "r"(b), "r"(c), "r"(d) : "memory");
}
__device__ __forceinline__ void mma16816(float (&d)[4], uint32_t a0, uint32_t a1, uint32_t a2, uint32_t a3, uint32_t b0, uint32_t b1) {
  asm volatile("mma.sync.aligned.m16n8k16.row.col.f32.bf16.bf16.f32 {%0, %1, %2, %3}, {%4, %5, %6, %7}, {%8, %9}, {%0, %1, %2, %3};"
               : "+f"(d[0]), "+f"(d[1]), "+f"(d[2]), "+f"(d[3]) : "r"(a0), "r"(a1), "r"(a2), "r"(a3), "r"(b0), "r"(b1));
}

#define TSTAMP(i)
#define GSTAMP(i)

#define DBGF(m) 0
struct Cx { float re, im; };
__device__ __forceinline__ Cx cmul(Cx a, Cx b) {
  Cx r;
  r.re = fmaf(a.re, b.re, -(a.im * b.im));
  r.im = fmaf(a.re, b.im, a.im * b.re);
  return r;
}
__device__ __forceinline__ Cx cexp_boot(float a2, float tr, float e) {
  float mag = exp2f(a2 * e);
  float t = tr * e;
  t -= rintf(t);
  float s, c;
  s = __sinf(t * 6.283185307179586f);
  c = __cosf(t * 6.283185307179586f);
  Cx r; r.re = mag * c; r.im = mag * s;
  return r;
}

struct Ptrs {
  const __nv_bfloat16 *u, *logA, *Aim, *Cre, *Cim, *logdt, *Dskip, *gatew, *w1, *w2;
};

struct KgRaw { uint32_t la, im, cr, ci; };
__device__ __forceinline__ uint32_t pack_h2(float lo, float hi) {
  uint32_t r;
  asm("cvt.rn.f16x2.f32 %0, %1, %2;" : "=r"(r) : "f"(hi), "f"(lo));
  return r;
}
struct H2c { uint32_t v, rot; };
__device__ __forceinline__ H2c h2c(Cx x) { H2c r; r.v = pack_h2(x.re, x.im); r.rot = pack_h2(-x.im, x.re); return r; }
__device__ __forceinline__ uint32_t hcmul(uint32_t a, const H2c& b) {
  const __half2 ah = *reinterpret_cast<const __half2*>(&a);
  const __half2 r = __hfma2(__high2half2(ah), *reinterpret_cast<const __half2*>(&b.rot),
                            __hmul2(__low2half2(ah), *reinterpret_cast<const __half2*>(&b.v)));
  return *reinterpret_cast<const uint32_t*>(&r);
}
__device__ __forceinline__ void mma16816_f16(float (&d)[4], uint32_t a0, uint32_t a1, uint32_t a2, uint32_t a3, uint32_t b0, uint32_t b1) {
  asm volatile("mma.sync.aligned.m16n8k16.row.col.f32.f16.f16.f32 {%0, %1, %2, %3}, {%4, %5, %6, %7}, {%8, %9}, {%0, %1, %2, %3};"
               : "+f"(d[0]), "+f"(d[1]), "+f"(d[2]), "+f"(d[3]) : "r"(a0), "r"(a1), "r"(a2), "r"(a3), "r"(b0), "r"(b1));
}
__device__ __forceinline__ void kgen_round(float (&acc)[5][4], float& k2048, const KgRaw& p, float dt, float cs, uint32_t kg, int lane) {
  const float are = -bf16r(expf(__uint_as_float(p.la << 16)));
  const float a2 = (are * dt) * 1.4426950408889634f;
  const float tr = (__uint_as_float(p.im << 16) * dt) * 0.15915494309189535f;
  const Cx C = {__uint_as_float(p.cr << 16) * cs, __uint_as_float(p.ci << 16) * cs};
  const uint32_t l7 = lane & 7;
  const uint32_t lmA = kg + (l7 + 8 * ((lane >> 3) & 1)) * 128, chA = lane >> 4;
  const uint32_t lmB = (l7 + 8 * (lane >> 4)) * 128, chB = (lane >> 3) & 1;
  const uint32_t lmB2 = l7 * 128;
  const uint32_t buf0 = kg, buf1 = kg + 2048;
  uint32_t sl[8];
#pragma unroll
  for (int r = 0; r < 8; r++) sl[r] = r * 128 + (((lane >> 2) ^ r) << 4) + (lane & 3) * 4;
  auto put = [&](uint32_t buf, int row, uint32_t v) { sts32(buf + sl[row & 7] + (row >> 3) * 1024, v); };
  const Cx w1 = cexp_boot(a2, tr, 1.f), W1 = cexp_boot(a2, tr, 128.f);
  Cx v1 = cexp_boot(a2, tr, 8.f);
  v1.im = -v1.im;
  const Cx v2 = cmul(v1, v1), v3 = cmul(v2, v1), v4 = cmul(v2, v2), v8 = cmul(v4, v4);
  const Cx w2 = cmul(w1, w1), w3 = cmul(w2, w1), w4 = cmul(w2, w2), w5 = cmul(w4, w1), w6 = cmul(w4, w2), w7 = cmul(w4, w3);
  const Cx W2 = cmul(W1, W1), W3 = cmul(W2, W1), W4 = cmul(W2, W2);
  const Cx X4 = cmul(C, W4), X8 = cmul(X4, W4), X12 = cmul(X8, W4);
  k2048 += fmaf(X12.re, W4.re, -(X12.im * W4.im));
  {
    const H2c h1 = h2c(v1), h2 = h2c(v2), h3 = h2c(v3), h8 = h2c(v8);
    const uint32_t a4 = pack_h2(v4.re, v4.im), a12 = hcmul(a4, h8);
    put(buf0, 0, pack_h2(1.f, 0.f)); put(buf0, 1, h1.v); put(buf0, 2, h2.v); put(buf0, 3, h3.v);
    put(buf0, 4, a4); put(buf0, 5, hcmul(a4, h1)); put(buf0, 6, hcmul(a4, h2)); put(buf0, 7, hcmul(a4, h3));
    put(buf0, 8, h8.v); put(buf0, 9, hcmul(h8.v, h1)); put(buf0, 10, hcmul(h8.v, h2)); put(buf0, 11, hcmul(h8.v, h3));
    put(buf0, 12, a12); put(buf0, 13, hcmul(a12, h1)); put(buf0, 14, hcmul(a12, h2)); put(buf0, 15, hcmul(a12, h3));
  }
  const H2c g1 = h2c(W1), g2 = h2c(W2), g3 = h2c(W3);
  const H2c b2 = h2c(w2), b4 = h2c(w4), b6 = h2c(w6);
  uint32_t x[16];
  x[0] = pack_h2(C.re, C.im); x[4] = pack_h2(X4.re, X4.im); x[8] = pack_h2(X8.re, X8.im); x[12] = pack_h2(X12.re, X12.im);
#pragma unroll
  for (int q = 0; q < 4; q++) { x[4 * q + 1] = hcmul(x[4 * q], g1); x[4 * q + 2] = hcmul(x[4 * q], g2); x[4 * q + 3] = hcmul(x[4 * q], g3); }
  {
    const H2c b1 = h2c(w1), b3 = h2c(w3), b5 = h2c(w5), b7 = h2c(w7);
#pragma unroll
    for (int a = 0; a < 2; a++) {
      put(buf1, 8 * a, x[a]);
      put(buf1, 8 * a + 1, hcmul(x[a], b1)); put(buf1, 8 * a + 2, hcmul(x[a], b2)); put(buf1, 8 * a + 3, hcmul(x[a], b3));
      put(buf1, 8 * a + 4, hcmul(x[a], b4)); put(buf1, 8 * a + 5, hcmul(x[a], b5)); put(buf1, 8 * a + 6, hcmul(x[a], b6));
      put(buf1, 8 * a + 7, hcmul(x[a], b7));
    }
  }
  __syncwarp();
  uint32_t af[4][4];
#pragma unroll
  for (int s = 0; s < 4; s++) ldsm4(lmA + (((2 * s + chA) ^ l7) << 4), af[s][0], af[s][1], af[s][2], af[s][3]);
#pragma unroll
  for (int s = 0; s < 4; s++) {
    uint32_t c0, c1, c2, c3;
    ldsm4(buf1 + lmB + (((2 * s + chB) ^ l7) << 4), c0, c1, c2, c3);
    mma16816_f16(acc[0], af[s][0], af[s][1], af[s][2], af[s][3], c0, c1);
    mma16816_f16(acc[1], af[s][0], af[s][1], af[s][2], af[s][3], c2, c3);
  }
  __syncwarp();
#pragma unroll
  for (int a = 0; a < 2; a++) {
    put(buf0, 4 * a, x[2 + a]); put(buf0, 4 * a + 1, hcmul(x[2 + a], b2));
    put(buf0, 4 * a + 2, hcmul(x[2 + a], b4)); put(buf0, 4 * a + 3, hcmul(x[2 + a], b6));
  }
#pragma unroll
  for (int a = 0; a < 4; a++) { put(buf0, 8 + 2 * a, x[4 + a]); put(buf0, 9 + 2 * a, hcmul(x[4 + a], b4)); }
#pragma unroll
  for (int a = 0; a < 8; a++) put(buf1, a, x[8 + a]);
  __syncwarp();
#pragma unroll
  for (int s = 0; s < 4; s++) {
    uint32_t c0, c1, c2, c3;
    ldsm4(buf0 + lmB + (((2 * s + chB) ^ l7) << 4), c0, c1, c2, c3);
    mma16816_f16(acc[2], af[s][0], af[s][1], af[s][2], af[s][3], c0, c1);
    mma16816_f16(acc[3], af[s][0], af[s][1], af[s][2], af[s][3], c2, c3);
    ldsm2(buf1 + lmB2 + (((2 * s + chB) ^ l7) << 4), c0, c1);
    mma16816_f16(acc[4], af[s][0], af[s][1], af[s][2], af[s][3], c0, c1);
  }
  __syncwarp();
}
__device__ __forceinline__ float kgen_scale(uint32_t cmax_bits) {
  const uint32_t e = cmax_bits >> 23;
  return (e == 0u || e >= 253u) ? 1.f : __uint_as_float((254u - e) << 23);
}
__device__ __forceinline__ uint32_t kgen_cmax(uint2 cr, uint2 ci) {
  uint32_t m = max(max(max(cr.x & 0x7fffu, (cr.x >> 16) & 0x7fffu), max(cr.y & 0x7fffu, (cr.y >> 16) & 0x7fffu)),
                   max(max(ci.x & 0x7fffu, (ci.x >> 16) & 0x7fffu), max(ci.y & 0x7fffu, (ci.y >> 16) & 0x7fffu)));
  m = __reduce_max_sync(0xffffffffu, m);
  return m << 16;
}

__device__ __forceinline__ uint32_t elem16(uint2 v, int q) { const uint32_t w = q < 2 ? v.x : v.y; return (q & 1) ? (w >> 16) : (w & 0xffffu); }
__device__ __forceinline__ void kgen_item(uint2 la, uint2 im, uint2 cr, uint2 ci, uint32_t ldt, int q0, int nr, uint32_t kg, uint32_t part_bar, bool publish, int lane, uint32_t sb) {
  if (threadIdx.x < 32) TSTAMP(74);
  const float cs = kgen_scale(kgen_cmax(cr, ci));
  if (threadIdx.x < 32) TSTAMP(75);
  const float dt = bf16r(expf(__uint_as_float(ldt << 16)));
  if (threadIdx.x < 32) TSTAMP(76);
  float acc[5][4];
#pragma unroll
  for (int t = 0; t < 5; t++) { acc[t][0] = acc[t][1] = acc[t][2] = acc[t][3] = 0.f; }
  float k2048 = 0.f;
#pragma unroll 1
  for (int q = 0; q < nr; q++) {
    const KgRaw r = {elem16(la, q0 + q), elem16(im, q0 + q), elem16(cr, q0 + q), elem16(ci, q0 + q)};
    kgen_round(acc, k2048, r, dt, cs, kg, lane);
    if (threadIdx.x < 32) TSTAMP(78 + q);
  }
#pragma unroll
  for (int t = 0; t < 5; t++)
#pragma unroll
    for (int i = 0; i < 4; i++) sts32(kg + ((4 * t + i) * 32 + lane) * 4, __float_as_uint(acc[t][i]));
  sts32(kg + (20 * 32 + lane) * 4, __float_as_uint(k2048));
  cluster_wait();
  __syncwarp();
  if (lane == 0 && publish) mbar_arrive(part_bar);
}
template <int N>
__device__ __forceinline__ void conv_wgmma(float (&acc)[32], const uint32_t* q, uint64_t db, int sc) {
  if (N == 64) wgmma_rs_n64(acc, q[0], q[1], q[2], q[3], db, sc);
  if (N == 56) wgmma_rs_n56(acc, q[0], q[1], q[2], q[3], db, sc);
  if (N == 48) wgmma_rs_n48(acc, q[0], q[1], q[2], q[3], db, sc);
  if (N == 40) wgmma_rs_n40(acc, q[0], q[1], q[2], q[3], db, sc);
  if (N == 32) wgmma_rs_n32(acc, q[0], q[1], q[2], q[3], db, sc);
  if (N == 24) wgmma_rs_n24(acc, q[0], q[1], q[2], q[3], db, sc);
  if (N == 16) wgmma_rs_n16(acc, q[0], q[1], q[2], q[3], db, sc);
  if (N == 8) wgmma_rs_n8(acc, q[0], q[1], q[2], q[3], db, sc);
}
template <int JN>
__device__ __forceinline__ void conv_ld(uint32_t (&q)[16], uint32_t qaddr) {
#pragma unroll
  for (int jj = 0; jj < JN; jj++) {
    uint32_t* p = q + 8 * jj;
    const uint32_t a = qaddr + jj * 256;
    p[1] = lds32(a);
    p[0] = lds32(a - 32);
    p[2] = lds32(a - 64);
    p[4] = lds32(a - 96);
    p[6] = lds32(a - 128);
  }
#pragma unroll
  for (int jj = 0; jj < JN; jj++) {
    uint32_t* p = q + 8 * jj;
    p[3] = p[0]; p[5] = p[2]; p[7] = p[4];
  }
}
template <int G, int G0, int G1>
__device__ __forceinline__ void conv_near(float (&acc)[32], uint32_t (&q)[2][16], uint32_t qaddr, uint32_t plbase) {
  if constexpr (G < G1) {
    constexpr int GG = G / 2;
    constexpr int N = GG == 1 ? 64 : 64 - 8 * GG;
    constexpr int JN = G == 8 ? 1 : 2;
    constexpr uint64_t KSTEP = (2 * PL_STRIDE) >> 4;
    const uint64_t db = mkdesc(plbase + 4 * G * 16, PL_STRIDE, 128, 0);
    wg_fence();
#pragma unroll
    for (int jj = 0; jj < JN; jj++) {
      conv_wgmma<N>(acc, &q[G & 1][8 * jj], db + 2 * jj, (G == G0 && jj == 0) ? 0 : 1);
      conv_wgmma<N>(acc, &q[G & 1][8 * jj + 4], db + 2 * jj + KSTEP, 1);
    }
    wg_commit();
    if ((G & 1) == 1 || G + 1 == G1) { wg_wait<0>(); reg_fence(acc); } else wg_wait<1>();
    if (G + 1 < G1) conv_ld<(G + 1 == 8) ? 1 : 2>(q[(G + 1) & 1], qaddr + (G + 1) * 512);
    conv_near<G + 1, G0, G1>(acc, q, qaddr, plbase);
  }
}
__device__ __forceinline__ void far_windows(uint32_t plb, uint32_t wb, int t128) {
  float v[32];
#pragma unroll
  for (int j = 0; j < 4; j++) {
    const int p = t128 - 3 + j;
    uint4 w = make_uint4(0u, 0u, 0u, 0u);
    if (p >= 0) w = lds128(plb + (p & 3) * PL_STRIDE + (63 - (p >> 2)) * 16);
    v[8 * j] = bf_lo(w.x); v[8 * j + 1] = bf_hi(w.x); v[8 * j + 2] = bf_lo(w.y); v[8 * j + 3] = bf_hi(w.y);
    v[8 * j + 4] = bf_lo(w.z); v[8 * j + 5] = bf_hi(w.z); v[8 * j + 6] = bf_lo(w.w); v[8 * j + 7] = bf_hi(w.w);
  }
  float a[8], b[8];
  a[0] = ((v[4] + v[5]) + (v[6] + v[7])) + ((v[8] + v[9]) + (v[10] + v[11])) + v[12];
  b[0] = ((v[13] + v[14]) + (v[15] + v[16])) + ((v[17] + v[18]) + v[19]);
#pragma unroll
  for (int i = 1; i < 8; i++) {
    a[i] = a[i - 1] + (v[12 + i] - v[3 + i]);
    b[i] = b[i - 1] + (v[19 + i] - v[12 + i]);
  }
  const uint32_t ad = wb + (t128 & 1) * WB_PLANE + (t128 >> 1) * 16;
  sts128(ad, pack_bf16(a[0], a[1]), pack_bf16(a[2], a[3]), pack_bf16(a[4], a[5]), pack_bf16(a[6], a[7]));
  sts128(ad + 2 * WB_PLANE, pack_bf16(b[0], b[1]), pack_bf16(b[2], b[3]), pack_bf16(b[4], b[5]), pack_bf16(b[6], b[7]));
}
__device__ __forceinline__ void far_ld(uint32_t (&q)[16], uint32_t qaddr) {
  q[1] = lds32(qaddr);
#pragma unroll
  for (int kk = 0; kk < 4; kk++) {
    q[4 * kk] = lds32(qaddr - 32 * (2 * kk + 1));
    q[4 * kk + 2] = lds32(qaddr - 32 * (2 * kk + 2));
  }
#pragma unroll
  for (int kk = 0; kk < 4; kk++) {
    q[4 * kk + 3] = q[4 * kk];
    if (kk) q[4 * kk + 1] = q[4 * kk - 2];
  }
}
__device__ __forceinline__ void conv_far(float (&d3)[8], uint32_t (&q)[2][16], uint32_t qslot_x, uint32_t wb) {
  far_ld(q[0], qslot_x + QE_OFF);
  far_ld(q[1], qslot_x + QO_OFF);
  const uint64_t db = mkdesc(wb, 128, WB_PLANE, 0);
  wg_fence();
#pragma unroll
  for (int kk = 0; kk < 4; kk++) wgmma_rs_n16_tb(d3, q[0][4 * kk], q[0][4 * kk + 1], q[0][4 * kk + 2], q[0][4 * kk + 3], db + 16 * kk, kk != 0);
#pragma unroll
  for (int kk = 0; kk < 4; kk++) wgmma_rs_n16_tb(d3, q[1][4 * kk], q[1][4 * kk + 1], q[1][4 * kk + 2], q[1][4 * kk + 3], db + ((2 * WB_PLANE) >> 4) + 16 * kk, 1);
  wg_commit();
  wg_wait<0>();
  reg_fence(d3);
}
__device__ __forceinline__ void far_store(const float (&d3)[8], uint32_t wb, int w, int r, int c) {
#pragma unroll
  for (int h = 0; h < 2; h++) {
    const int sw = (((r >> 2) & 1) | (h << 1)) << 3;
#pragma unroll
    for (int i = 0; i < 2; i++) {
      const int word = (256 * w + 128 * h + 16 * r + 8 * i + 2 * c) ^ sw;
      asm volatile("st.shared.v2.f32 [%0], {%1, %2};" ::"r"(wb + word * 4), "f"(d3[4 * i + 2 * h]), "f"(d3[4 * i + 2 * h + 1]) : "memory");
    }
  }
}

__device__ __forceinline__ void role_builder(const Ptrs& P, uint32_t sb, int cta, int ch, int warp, int lane) {
  auto BAR = [&](int i) { return sb + OFF_BAR + 8 * i; };
      if (warp == 9) TSTAMP(124);
      const uint32_t ldt_own = ldg16_nc(P.logdt + cta * 5 + ch);
      const uint32_t dsk_own = ldg16_nc(P.Dskip + cta * 5 + ch);
      const uint2 own_cr = ldg64_nc(P.Cre + (cta * 5 + ch) * NMODE + 4 * lane), own_ci = ldg64_nc(P.Cim + (cta * 5 + ch) * NMODE + 4 * lane);
      mbar_wait(BAR(BAR_PART + ch), 0);
      float acc[5][4], k2048 = 0.f;
#pragma unroll
      for (int t = 0; t < 5; t++) { acc[t][0] = acc[t][1] = acc[t][2] = acc[t][3] = 0.f; }
      {
        const int pb0 = 2 * ch, np = ch < 4 ? 2 : 4;
#pragma unroll 1
        for (int pi = 0; pi < np; pi++) {
          const uint32_t pb = sb + OFF_KB + (pb0 + pi) * 4096 + lane * 4;
#pragma unroll
          for (int t = 0; t < 5; t++)
#pragma unroll
            for (int i = 0; i < 4; i++) acc[t][i] += __uint_as_float(lds32(pb + (4 * t + i) * 128));
          k2048 += __uint_as_float(lds32(pb + 20 * 128));
        }
      }
#pragma unroll
      for (int o = 16; o; o >>= 1) k2048 += __shfl_xor_sync(0xffffffffu, k2048, o);
      const uint32_t kg = sb + OFF_KC + ch * KC_BYTES;
      const float dt = bf16r(expf(__uint_as_float(ldt_own << 16)));
      const float sc = 2.f * dt / kgen_scale(kgen_cmax(own_cr, own_ci));
      {
        const int g = lane >> 2, c = lane & 3;
#pragma unroll
        for (int h = 0; h < 2; h++) {
          const int i = g + 8 * h;
          const float k0 = (h == 0 && lane == 0) ? fmaf(sc, acc[0][0], __uint_as_float(dsk_own << 16)) : sc * acc[0][2 * h];
          sts32(kg + (8 * i + 2 * c) * 2, pack_bf16(k0, sc * acc[0][2 * h + 1]));
          sts32(kg + (128 + 8 * i + 2 * c) * 2, pack_bf16(sc * acc[1][2 * h], sc * acc[1][2 * h + 1]));
          sts32(kg + (256 + 4 * i + 64 * (c >> 1) + 2 * (c & 1)) * 2, pack_bf16(sc * acc[2][2 * h], sc * acc[2][2 * h + 1]));
          sts32(kg + (384 + 2 * i + 32 * c) * 2, pack_bf16(sc * acc[3][2 * h], sc * acc[3][2 * h + 1]));
          const uint32_t p4 = pack_bf16(sc * acc[4][2 * h], sc * acc[4][2 * h + 1]);
          sts16(kg + (512 + i + 32 * c) * 2, p4 & 0xffffu);
          sts16(kg + (512 + i + 32 * c + 16) * 2, p4 >> 16);
        }
        if (lane == 0) sts16(kg + 640 * 2, pack_bf16(sc * k2048, 0.f) & 0xffffu);
      }
      __syncwarp();
      named_sync(6, 160);
      {
        const uint32_t q = sb + OFF_Q + ch * Q_BYTES + Q_PAD * 4;
        sts32(q - 128 + lane * 4, 0u);
        {
          const uint4 w = lds128(kg + lane * 16);
          const uint32_t pv = lane ? (lds16(kg + lane * 16 - 2) << 16) : 0u;
          sts128(q + lane * 32, __byte_perm(w.x, pv, 0x7610), __byte_perm(w.x, w.x, 0x1032), __byte_perm(w.y, w.x, 0x7610), __byte_perm(w.y, w.y, 0x1032));
          sts128(q + lane * 32 + 16, __byte_perm(w.z, w.y, 0x7610), __byte_perm(w.z, w.z, 0x1032), __byte_perm(w.w, w.z, 0x7610), __byte_perm(w.w, w.w, 0x1032));
        }
        {
          const uint2 w = lds64(kg + (256 + 4 * lane) * 2);
          const uint32_t v4 = lds16(kg + (256 + 4 * lane + 4) * 2);
          const uint32_t pv = lane ? (w.x & 0xffffu) : lds16(kg + 255 * 2);
          const uint32_t v0 = w.x & 0xffffu, v1 = w.x >> 16, v2 = w.y & 0xffffu, v3 = w.y >> 16;
          const uint32_t a = q + (256 + 8 * lane) * 4;
          sts128(a, v0 | (pv << 16), v0 | (v0 << 16), v1 | (v0 << 16), v2 | (v1 << 16));
          sts128(a + 16, v2 | (v2 << 16), v2 | (v2 << 16), v3 | (v2 << 16), v4 | (v3 << 16));
        }
#pragma unroll
        for (int t = 0; t < 2; t++) {
          const int m = lane + 32 * t;
          const uint32_t w = lds32(kg + (384 + 2 * m) * 2);
          const uint32_t A = w & 0xffffu, B = w >> 16, Cc = lds16(kg + (384 + 2 * m + 2) * 2);
          const uint32_t AA = A | (A << 16), BB = B | (B << 16);
          const uint32_t a = q + (512 + 8 * m) * 4;
          sts128(a, AA, AA, AA, B | (A << 16));
          sts128(a + 16, BB, BB, Cc | (B << 16), Cc | (Cc << 16));
        }
        {
          const uint32_t A = lds16(kg + 512 * 2);
          const int x0 = 1024 + 2 * lane;
          const uint32_t w0 = (x0 <= 1028 ? A : 0u) | (x0 <= 1029 ? (A << 16) : 0u);
          const uint32_t w1 = (x0 + 1 <= 1028 ? A : 0u) | (x0 + 1 <= 1029 ? (A << 16) : 0u);
          sts32(q + x0 * 4, w0);
          sts32(q + x0 * 4 + 4, w1);
        }
        {
          const uint32_t qe = sb + OFF_Q + ch * Q_BYTES + QE_OFF, qo = sb + OFF_Q + ch * Q_BYTES + QO_OFF;
          sts32(qe - 256 + lane * 4, 0u); sts32(qe - 128 + lane * 4, 0u);
          sts32(qo - 256 + lane * 4, 0u); sts32(qo - 128 + lane * 4, 0u);
#pragma unroll
          for (int t = 0; t < 2; t++) {
            const int m = lane + 32 * t;
            const uint32_t e0 = lds16(kg + (514 + 2 * m) * 2), o0 = lds16(kg + (513 + 2 * m) * 2);
            const uint32_t e1 = m ? lds16(kg + (512 + 2 * m) * 2) : 0u, o1 = m ? lds16(kg + (511 + 2 * m) * 2) : 0u;
            sts32(qe + m * 4, e0 | (e1 << 16));
            sts32(qo + m * 4, o0 | (o1 << 16));
          }
        }
      }
      __syncwarp();
      if (lane == 0) mbar_arrive(BAR(BAR_QREADY + ch));
      TSTAMP(8 + ch);
}

__global__ void __cluster_dims__(2, 1, 1) __launch_bounds__(NTHREADS, 1)
fused_kernel(const __grid_constant__ CUtensorMap tm_x, const __grid_constant__ CUtensorMap tm_w1a,
             const __grid_constant__ CUtensorMap tm_w1b, const __grid_constant__ CUtensorMap tm_slab,
             const __grid_constant__ CUtensorMap tm_hst, const __grid_constant__ CUtensorMap tm_hld,
             const __grid_constant__ CUtensorMap tm_w2, const __grid_constant__ CUtensorMap tm_aT, const __grid_constant__ CUtensorMap tm_ast,
             const __grid_constant__ CUtensorMap tm_out, const Ptrs P) {
  extern __shared__ __align__(1024) uint8_t smem_raw[];
  const uint32_t sb = smem_u32(smem_raw);
  const uint32_t bar0 = sb + OFF_BAR;
  auto BAR = [&](int i) { return bar0 + 8 * i; };
  const int tid = threadIdx.x, warp = __shfl_sync(0xffffffffu, tid >> 5, 0), lane = tid & 31;
  const int cta = blockIdx.x, rank = cta & 1, cl = cta >> 1;
  const int i1 = 2 * (cl >> 3) + rank, j1 = cl & 7;
  const int i2 = cl & 15, n2 = cl >> 4;

  if (warp == 8) { TSTAMP(64); GSTAMP(65); }
  const bool kact = warp < 8 || (warp >= 9 && warp < 13);
  const int kch = warp < 8 ? (warp >> 1) : 4;
  const int kq = warp < 8 ? 2 * (warp & 1) : warp - 9;
  const int kbuf = warp < 8 ? warp : warp - 1;
  uint2 kla = {}, kim = {}, kcr = {}, kci = {};
  uint32_t ldt = 0;
  if (kact) {
    const int d = cta * 5 + kch;
    kcr = ldg64_nc(P.Cre + d * NMODE + 4 * lane);
    kci = ldg64_nc(P.Cim + d * NMODE + 4 * lane);
    kla = ldg64_nc(P.logA + d * NMODE + 4 * lane);
    kim = ldg64_nc(P.Aim + d * NMODE + 4 * lane);
    ldt = ldg16_nc(P.logdt + d);
    if (warp == 9) TSTAMP(120);
  }
  if (lane == 0 && warp >= 8 && warp != 13) {
    if (warp == 8) {
      mbar_init(BAR(BAR_FULL1), 1);
      mbar_expect_tx(BAR(BAR_FULL1), A1_BYTES);
      tma_ld2(sb + OFF_RING, &tm_x, BAR(BAR_FULL1), 0, i1 * 128);
      prefetch_tmap(rank ? &tm_w1b : &tm_w1a);
      for (int s = 1; s < S1; s++) mbar_init(BAR(BAR_FULL1 + s), 1);
      for (int s = 0; s < S1; s++) mbar_init(BAR(BAR_EMPTY1 + s), 8);
    } else if (warp == 9) {
      for (int s = 0; s < SB1; s++) mbar_init(BAR(BAR_FULLB + s), 1);
    } else if (warp == 10) {
      for (int s = 0; s < SB1; s++) mbar_init(BAR(BAR_EMPTYB + s), 16);
    } else if (warp == 11) {
      for (int c = 0; c < 4; c++) mbar_init(BAR(BAR_PART + c), 2);
      mbar_init(BAR(BAR_PART + 4), 4);
    } else if (warp == 12) {
      mbar_init(BAR(BAR_CONVDONE), 1);
      mbar_init(BAR(BAR_CONVDONE + 1), 1);
      mbar_init(BAR(BAR_AFULL), 1);
      mbar_init(BAR(BAR_HST), 4);
      mbar_init(BAR(BAR_HST + 1), 4);
      mbar_init(BAR(BAR_SEEN), 2);
    } else if (warp == 14) {
      for (int s = 0; s < S2; s++) { mbar_init(BAR(BAR_FULL2 + s), 1); mbar_init(BAR(BAR_EMPTY2 + s), 8); }
      mbar_init(BAR(BAR_SLAB), 1);
    } else {
      mbar_init(BAR(BAR_RINGFREE), 4);
      mbar_init(BAR(BAR_UFULL), 1);
      for (int c = 0; c < 5; c++) mbar_init(BAR(BAR_QREADY + c), 1);
    }
    asm volatile("fence.mbarrier_init.release.cluster;" ::: "memory");
    if (warp == 8) TSTAMP(121);
  }
  if (tid == 448) prefetch_tmap(&tm_slab);
  __syncwarp();
  asm volatile("barrier.cluster.arrive.relaxed.aligned;" ::: "memory");
  if (warp == 8) TSTAMP(123);
  if (kact || warp == 13) kgen_item(kla, kim, kcr, kci, ldt, kq & 3, warp < 8 ? 2 : 1, sb + OFF_KB + kbuf * 4096, BAR(BAR_PART + kch), warp != 13, lane, sb);
  else cluster_wait();
  if (warp < 8) TSTAMP(16 + warp);

  if (warp >= 12) {
    asm volatile("setmaxnreg.dec.sync.aligned.u32 112;");
    constexpr unsigned tag = 1u;
    if (warp < 14) {
      role_builder(P, sb, cta, warp - 9, warp, lane);
    } else {
      const int w2 = warp - 14;
      const int sp = cta >> 2, kap = cta & 3;
      const uint32_t slab = sb + OFF_PL;
      if (!DBGF(2)) {
      if (w2 == 0 && lane == 0) {
        mbar_wait(BAR(BAR_FULL1), 0);
        l2_prefetch((const uint8_t*)P.w1 + (size_t)cta * (5 * F_ * 2), 5 * F_ * 2);
        mbar_expect_tx(BAR(BAR_SLAB), 16 * D_ * 2);
        tma_ld4(slab, &tm_slab, BAR(BAR_SLAB), 0, 8 * kap, 2 * sp, 0);
      }
      mbar_wait(BAR(BAR_SLAB), 0);
      if (w2 == 0) TSTAMP(68);
      {
        const int mi = lane >> 3, i = lane & 7;
        const int rho = (i >> 1) * 4 + (i & 1) + 2 * (mi & 1);
        const int ri = rho & 7;
        const uint32_t la = slab + (1 - (rho >> 3)) * 1024 + ri * 128;
        const int g = lane >> 2, c = lane & 3;
        uint8_t* dst = (uint8_t*)g_up + (size_t)(g + 16 * w2) * PLCH_BYTES + kap * PL_STRIDE + (31 - sp) * 32 + c * 8;
#pragma unroll 5
        for (int it = 0; it < 20; it++) {
          const int chunk = (it & 1) * 4 + w2 * 2 + (mi >> 1);
          uint32_t r0, r1, r2, r3;
          ldsm4t(la + (it >> 1) * 2048 + ((chunk ^ ri) << 4), r0, r1, r2, r3);
          *(uint2*)(dst + (size_t)it * (32 * PLCH_BYTES)) = make_uint2(r0, r1);
          *(uint2*)(dst + (size_t)it * (32 * PLCH_BYTES) + 8 * PLCH_BYTES) = make_uint2(r2, r3);
        }
      }
      }
      if (w2 == 0) TSTAMP(69);
      named_sync(8, 64);
      if (w2 == 0 && lane == 0) cnt_arrive(CNT_U);
      if (w2 == 0) TSTAMP(4);
      if (w2 == 0) {
        if (lane == 0) {
          cnt_wait(CNT_U, NCTA);
          mbar_arrive(BAR(BAR_SEEN));
          TSTAMP(71);
          fence_async();
          mbar_expect_tx(BAR(BAR_UFULL), 5 * PLCH_BYTES);
          bulk_ld(sb + OFF_PL, (const uint8_t*)g_up + (size_t)(cta * 5) * PLCH_BYTES, 5 * PLCH_BYTES, BAR(BAR_UFULL));
        }
        TSTAMP(6);
      }
    }
    {
      const int tid = fresh_tid(), lane = tid & 31;
        float acc[80];
#pragma unroll
        for (int i = 0; i < 80; i++) acc[i] = 0.f;
#pragma unroll 1
        for (int ks = 0; ks < NK2; ks++) {
          const int s = ks % S2;
          mbar_wait(BAR(BAR_FULL2 + s), (ks / S2) & 1);
          const uint32_t st = sb + OFF_RING + s * ST2_BYTES;
          const uint64_t da = mkdesc(st, 16, 1024, 1);
          const uint64_t db = mkdesc(st + A2_BYTES, B2_BLK, 512, 2);
          wg_fence();
#pragma unroll
          for (int kk = 0; kk < 4; kk++)
            wgmma_ss_n160_tb(acc, da + 2 * kk, db + ((kk >> 1) * B2_HALF + (kk & 1) * 1024) / 16, 1);
          wg_commit();
          if (ks > 0) {
            wg_wait<1>();
            if (ks - 1 + S2 < NK2 && lane < 2) mbar_arrive_cta(BAR(BAR_EMPTY2 + (ks - 1) % S2), lane);
          }
        }
        wg_wait<0>();
        reg_fence(acc);
        if (warp == 12) TSTAMP(126);
        const int w = (tid >> 5) & 3, r = lane >> 2;
        mbar_wait(BAR(BAR_AFULL), 0);
        const float g0 = __uint_as_float(lds32(sb + OFF_PL + 2 * 80 * 128 + (16 * w + r) * 4));
        const float g1 = __uint_as_float(lds32(sb + OFF_PL + 2 * 80 * 128 + (16 * w + r + 8) * 4));
        const uint32_t gg[2] = {pack_bf16(g0, g0), pack_bf16(g1, g1)};
        const uint32_t og[2] = {pack_bf16(1.f - g0, 1.f - g0), pack_bf16(1.f - g1, 1.f - g1)};
        const int mi = lane >> 3, jj = lane & 7, h = mi & 1;
        named_sync(9, 128);
#pragma unroll
        for (int half = 0; half < 2; half++) {
          const uint32_t at = sb + OFF_PL + half * (80 * 128);
          const uint32_t os = sb + OFF_RING + half * (64 * 160);
#pragma unroll
          for (int i = 0; i < 10; i += 2) {
            const int dl = 8 * (i + (mi >> 1)) + jj, ia = 40 * half + 4 * i;
            uint32_t a0, a1, a2, a3;
            ldsm4t(at + dl * 128 + (((2 * w + h) ^ jj) << 4), a0, a1, a2, a3);
            const uint32_t o0 = badd2(bmul2(gg[0], a0), bmul2(og[0], pack_bf16(acc[ia], acc[ia + 1])));
            const uint32_t o1 = badd2(bmul2(gg[1], a1), bmul2(og[1], pack_bf16(acc[ia + 2], acc[ia + 3])));
            const uint32_t o2 = badd2(bmul2(gg[0], a2), bmul2(og[0], pack_bf16(acc[ia + 4], acc[ia + 5])));
            const uint32_t o3 = badd2(bmul2(gg[1], a3), bmul2(og[1], pack_bf16(acc[ia + 6], acc[ia + 7])));
            stsm4(os + (16 * w + 8 * h + jj) * 160 + (i + (mi >> 1)) * 16, o0, o1, o2, o3);
          }
          fence_async_smem();
          named_sync(9, 128);
          if (tid == 384) {
            tma_st2(&tm_out, os, n2 * 160 + half * 80, i2 * 128 + rank * 64);
            bulk_commit();
          }
        }
        if (tid == 384) bulk_wait_read();
        if (warp == 12) TSTAMP(56);
    }
  } else if (warp >= 8) {
    asm volatile("setmaxnreg.dec.sync.aligned.u32 80;");
    constexpr unsigned tag = 1u;
    if (warp == 8) {
      if (lane == 0) {
        TSTAMP(0);
        for (int hs = 0; hs < 2 * NK1; hs++) {
          if ((hs & 1) == 0 && hs > 0) {
            const int ks = hs >> 1, s = ks % S1;
            if (ks >= S1) mbar_wait(BAR(BAR_EMPTY1 + s), ((ks / S1) & 1) ^ 1);
            mbar_expect_tx(BAR(BAR_FULL1 + s), A1_BYTES);
            tma_ld2(sb + OFF_RING + s * A1_BYTES, &tm_x, BAR(BAR_FULL1 + s), ks * 64, i1 * 128);
          }
          const int s = hs % SB1;
          const uint32_t st = sb + OFF_RING + OFF_B1 + s * B1_BYTES, fb = BAR(BAR_FULLB + s);
          if (hs >= SB1) mbar_wait(BAR(BAR_EMPTYB + s), ((hs / SB1) & 1) ^ 1);
          mbar_expect_tx(fb, B1_BYTES);
          if (rank == 0) tma_ld3_mc(st, &tm_w1a, fb, 0, hs * 32, 7 * j1);
          else tma_ld3_mc(st + 4 * B1_BLK, &tm_w1b, fb, 0, hs * 32, 7 * j1 + 4);
        }
        TSTAMP(1);
        l2_prefetch((const uint8_t*)P.w2 + (size_t)cta * (F_ * D_ * 2 / NCTA), F_ * D_ * 2 / NCTA);
        prefetch_tmap(&tm_hld); prefetch_tmap(&tm_w2); prefetch_tmap(&tm_hst); prefetch_tmap(&tm_aT); prefetch_tmap(&tm_ast); prefetch_tmap(&tm_out);
      }
      __syncwarp();
      mbar_wait(BAR(BAR_RINGFREE), 0);
      if (lane == 0) {
        TSTAMP(122);
        for (int ks = 0; ks < S2; ks++) {
          const uint32_t st = sb + OFF_RING + ks * ST2_BYTES, fb = BAR(BAR_FULL2 + ks);
          mbar_expect_tx(fb, ST2_BYTES);
          tma_ld4_mc(st + A2_BYTES + rank * B2_HALF, &tm_w2, fb, 0, ks * 64 + rank * 32, 0, n2);
        }
      }
      if (lane == 0) {
        cnt_wait(CNT_H + 2 * i2 + rank, 8);
        mbar_arrive(BAR(BAR_SEEN));
        TSTAMP(83);
        fence_async();
        TSTAMP(2);
        for (int ks = 0; ks < NK2; ks++) {
          const int s = ks % S2;
          const uint32_t st = sb + OFF_RING + s * ST2_BYTES, fb = BAR(BAR_FULL2 + s);
          if (ks >= S2) {
            mbar_wait(BAR(BAR_EMPTY2 + s), ((ks / S2) & 1) ^ 1);
            mbar_expect_tx(fb, ST2_BYTES);
            tma_ld4_mc(st + A2_BYTES + rank * B2_HALF, &tm_w2, fb, 0, ks * 64 + rank * 32, 0, n2);
          }
          tma_ld2(st, &tm_hld, fb, ks * 64, i2 * 128 + rank * 64);
        }
        TSTAMP(3);
      }
    } else {
      role_builder(P, sb, cta, warp - 9, warp, lane);
      if (warp == 9) {
        if (lane < 2) {
          mbar_wait(BAR(BAR_HST + lane), 0);
          TSTAMP(82);
          tma_st3(&tm_hst, sb + OFF_RING + lane * HST_BYTES, 0, i1 * 128 + lane * 64, 7 * j1);
          bulk_commit();
          bulk_wait_read();
          mbar_arrive_cta(BAR(BAR_RINGFREE), 0);
          mbar_arrive_cta(BAR(BAR_RINGFREE), 1);
          TSTAMP(80);
          bulk_wait_all();
          TSTAMP(81);
          cnt_arrive_after_bulk(CNT_H + 2 * i1 + lane);
        }
        TSTAMP(5);
      } else if (warp == 10) {
        uint2 gw[5];
#pragma unroll
        for (int i = 0; i < 5; i++) gw[i] = ((const uint2*)P.gatew)[lane + 32 * i];
        float s[16];
#pragma unroll
        for (int r0 = 0; r0 < 16; r0 += 2) {
          uint2 xv[2][5];
#pragma unroll
          for (int r = 0; r < 2; r++)
#pragma unroll
            for (int i = 0; i < 5; i++) xv[r][i] = __ldg((const uint2*)(P.u + (size_t)(16 * cta + r0 + r) * D_) + lane + 32 * i);
#pragma unroll
          for (int r = 0; r < 2; r++) {
            float s0 = 0.f, s1 = 0.f;
#pragma unroll
            for (int i = 0; i < 5; i++) {
              const uint32_t p0 = bmul2(xv[r][i].x, gw[i].x), p1 = bmul2(xv[r][i].y, gw[i].y);
              s0 += bf_lo(p0); s1 += bf_hi(p0);
              s0 += bf_lo(p1); s1 += bf_hi(p1);
            }
            s[r0 + r] = s0 + s1;
          }
        }
#pragma unroll
        for (int lv = 0; lv < 4; lv++) {
          const int st = 8 >> lv;
          const bool up = lane & st;
#pragma unroll
          for (int i = 0; i < 8; i++) {
            if (i < st) {
              const float mine = up ? s[i + st] : s[i], oth = up ? s[i] : s[i + st];
              s[i] = mine + __shfl_xor_sync(0xffffffffu, oth, st);
            }
          }
        }
        s[0] += __shfl_xor_sync(0xffffffffu, s[0], 16);
        if (lane < 16) g_gate[16 * cta + lane] = bf16r(1.f / (1.f + expf(-bf16r(s[0]))));
        __syncwarp();
        if (lane == 0) cnt_arrive(CNT_G + (cta >> 2));
        TSTAMP(70);
      } else {
        if (lane == 0) {
          cnt_wait(CNT_G + 2 * i2 + rank, 4);
          mbar_wait(BAR(BAR_CONVDONE + 1), 0);
          mbar_wait(BAR(BAR_CONVDONE), 0);
          TSTAMP(84);
          cnt_wait(CNT_A + n2, 64);
          TSTAMP(85);
          fence_async();
          mbar_expect_tx(BAR(BAR_AFULL), 2 * 80 * 128 + 256);
          bulk_ld(sb + OFF_PL + 2 * 80 * 128, g_gate + i2 * 128 + rank * 64, 256, BAR(BAR_AFULL));
          tma_ld2(sb + OFF_PL, &tm_aT, BAR(BAR_AFULL), i2 * 128 + rank * 64, n2 * 160);
          tma_ld2(sb + OFF_PL + 80 * 128, &tm_aT, BAR(BAR_AFULL), i2 * 128 + rank * 64, n2 * 160 + 80);
          TSTAMP(7);
          mbar_wait(BAR(BAR_SEEN), 0);
          if (atomicAdd(&g_done, 1u) == NCTA - 1) {
            for (int i = 0; i < CNT_COUNT; i++) g_cnt[i * 32] = 0u;
            g_done = 0u;
          }
        }
      }
    }
  } else {
    asm volatile("setmaxnreg.inc.sync.aligned.u32 160;");
    constexpr unsigned tag = 1u;
    {
      const int tid = fresh_tid(), lane = tid & 31, warp = __shfl_sync(0xffffffffu, tid >> 5, 0);
      const int wg = warp >> 2, w = warp & 3;
      float acc[112];
#pragma unroll
      for (int i = 0; i < 112; i++) acc[i] = 0.f;
      const int arow = wg * 64 + 16 * w + (lane & 7) + 8 * ((lane >> 3) & 1);
      const uint32_t aoff = arow * 128, asw = arow & 7, ach = lane >> 4;
      uint32_t a0[8], a1[8];
#pragma unroll 1
      for (int ks = 0; ks < NK1; ks++) {
        const int s = ks % S1, h0 = 2 * s;
        const int pb = (ks / S1) & 1;
        constexpr uint64_t HI = (4 * B1_BLK) >> 4;
        const uint32_t sa = sb + OFF_RING + s * A1_BYTES + aoff;
        const uint64_t db0 = mkdesc(sb + OFF_RING + OFF_B1 + h0 * B1_BYTES, B1_BLK, 512, 2);
        const uint64_t db1 = db0 + (B1_BYTES >> 4);
        mbar_wait(BAR(BAR_FULL1 + s), (ks / S1) & 1);
        ldsm4(sa + ((ach ^ asw) << 4), a0[0], a0[1], a0[2], a0[3]);
        ldsm4(sa + (((ach + 2) ^ asw) << 4), a0[4], a0[5], a0[6], a0[7]);
        mbar_wait(BAR(BAR_FULLB + h0), pb);
        TSTAMP(warp == 0 ? 100 + ks : 127);
        wg_fence();
        wgmma_rs_n128_tb(acc, a0[0], a0[1], a0[2], a0[3], db0, 1);
        wgmma_rs_n96_tb(acc, a0[0], a0[1], a0[2], a0[3], db0 + HI, 1);
        wgmma_rs_n128_tb(acc, a0[4], a0[5], a0[6], a0[7], db0 + 64, 1);
        wgmma_rs_n96_tb(acc, a0[4], a0[5], a0[6], a0[7], db0 + 64 + HI, 1);
        wg_commit();
        wg_wait<1>();
        if (ks > 0 && 2 * ks - 1 + SB1 < 2 * NK1 && lane < 2) mbar_arrive_cta(BAR(BAR_EMPTYB + (2 * ks - 1) % SB1), lane);
        ldsm4(sa + (((ach + 4) ^ asw) << 4), a1[0], a1[1], a1[2], a1[3]);
        ldsm4(sa + (((ach + 6) ^ asw) << 4), a1[4], a1[5], a1[6], a1[7]);
        mbar_wait(BAR(BAR_FULLB + h0 + 1), pb);
        wg_fence();
        wgmma_rs_n128_tb(acc, a1[0], a1[1], a1[2], a1[3], db1, 1);
        wgmma_rs_n96_tb(acc, a1[0], a1[1], a1[2], a1[3], db1 + HI, 1);
        wgmma_rs_n128_tb(acc, a1[4], a1[5], a1[6], a1[7], db1 + 64, 1);
        wgmma_rs_n96_tb(acc, a1[4], a1[5], a1[6], a1[7], db1 + 64 + HI, 1);
        wg_commit();
        if (ks + S1 < NK1 && lane == 0) mbar_arrive(BAR(BAR_EMPTY1 + s));
        wg_wait<1>();
        if (2 * ks + SB1 < 2 * NK1 && lane < 2) mbar_arrive_cta(BAR(BAR_EMPTYB + h0), lane);
      }
      wg_wait<0>();
      reg_fence(acc);
      TSTAMP(24 + warp);
      named_sync(7, 256);
      const int hrow = 16 * w + 8 * ((lane >> 3) & 1) + (lane & 7);
      const uint32_t hst = sb + OFF_RING + wg * HST_BYTES + hrow * 64, hsw = (hrow >> 1) & 3, hch = lane >> 4;
#pragma unroll
      for (int i = 0; i < 28; i += 2)
        stsm4(hst + (i >> 2) * 4096 + ((((i & 3) + hch) ^ hsw) << 4),
              pack_bf16_relu(acc[4 * i], acc[4 * i + 1]), pack_bf16_relu(acc[4 * i + 2], acc[4 * i + 3]),
              pack_bf16_relu(acc[4 * i + 4], acc[4 * i + 5]), pack_bf16_relu(acc[4 * i + 6], acc[4 * i + 7]));
      fence_async_smem();
      __syncwarp();
      if (lane == 0) mbar_arrive(BAR(BAR_HST + wg));
    }
    {
    const int tid = fresh_tid(), lane = tid & 31, warp = __shfl_sync(0xffffffffu, tid >> 5, 0), wg = warp >> 2, w = warp & 3;
    const int r = lane >> 2, c = lane & 3;
    mbar_wait(BAR(BAR_UFULL), 0);
#pragma unroll 1
    for (int ch = 0; ch < 5; ch++) mbar_wait(BAR(BAR_QREADY + ch), 0);

#pragma unroll 1
    for (int ci = 0; ci < 3; ci++) {
      const int ch = ci < 2 ? 2 * ci + wg : 4;
      const int d = cta * 5 + ch;
      if (w == 0) TSTAMP(110 + ch);
      const uint32_t plb = sb + OFF_PL + ch * PLCH_BYTES;
      const uint32_t qaddr = sb + OFF_Q + ch * Q_BYTES + (Q_PAD + 16 * w + (r - 2 * c) + 8) * 4;
      float acc[32], d3[8];
      uint32_t qf[2][16];
      const uint32_t qx = sb + OFF_Q + ch * Q_BYTES + (16 * w + (r - 2 * c) + 8) * 4;
      const bool do_far = ci < 2 || wg == 1;
      const uint32_t wb = sb + OFF_WB + wg * WB_BYTES;
      auto far_part = [&]() {
        far_windows(plb, wb, tid & 127);
        fence_async_smem();
        named_sync(2 + wg, 128);
        conv_far(d3, qf, qx, wb);
        named_sync(2 + wg, 128);
        far_store(d3, wb, w, r, c);
      };
      if (do_far && (wg == 1 || ci == 2)) far_part();
      if (ci < 2) {
        conv_ld<2>(qf[0], qaddr);
        conv_near<0, 0, 9>(acc, qf, qaddr, plb);
        reg_fence(acc);
        if (wg == 0) far_part();
        reg_fence(acc);
      } else {
        const uint32_t hb0 = sb + OFF_YS + YS_BYTES + (tid & 127) * 16, hb1 = sb + OFF_HO + (tid & 127) * 16;
        if (wg == 1) {
          conv_ld<2>(qf[1], qaddr + 5 * 512);
          conv_near<5, 5, 9>(acc, qf, qaddr, plb);
#pragma unroll
          for (int i = 0; i < 6; i++)
            sts128(i < 4 ? hb0 + i * 2048 : hb1 + (i - 4) * 2048, __float_as_uint(acc[4 * i]), __float_as_uint(acc[4 * i + 1]),
                   __float_as_uint(acc[4 * i + 2]), __float_as_uint(acc[4 * i + 3]));
          named_sync(7, 256);
          break;
        }
        conv_ld<2>(qf[0], qaddr);
        conv_near<0, 0, 5>(acc, qf, qaddr, plb);
        named_sync(7, 256);
#pragma unroll
        for (int i = 0; i < 6; i++) {
          const uint4 v = lds128(i < 4 ? hb0 + i * 2048 : hb1 + (i - 4) * 2048);
          acc[4 * i] += __uint_as_float(v.x); acc[4 * i + 1] += __uint_as_float(v.y);
          acc[4 * i + 2] += __uint_as_float(v.z); acc[4 * i + 3] += __uint_as_float(v.w);
        }
      }
      if (w == 0) TSTAMP(115 + ch);
      {
      const int lane = fresh_tid() & 31, r = lane >> 2, c = lane & 3;
      const uint32_t zrow = sb + OFF_YS + wg * YS_BYTES + (16 * (w & 1) + r) * 256;
      const int zsw = ((r & 3) << 3) | (r >> 2);
      if (w >= 2) {
#pragma unroll
        for (int i = 0; i < 8; i++) {
#pragma unroll
          for (int h = 0; h < 2; h++) {
            const int n0 = 8 * i + 2 * c;
            if (i > 0 || c > 0) sts32(zrow + h * 2048 + (((n0 - 1) ^ zsw) << 2), __float_as_uint(acc[4 * i + 2 * h]));
            sts32(zrow + h * 2048 + ((n0 ^ zsw) << 2), __float_as_uint(acc[4 * i + 2 * h + 1]));
          }
        }
      }
      named_sync(2 + wg, 128);
      if (w < 2) {
#pragma unroll
        for (int i = 0; i < 8; i++) {
#pragma unroll
          for (int h = 0; h < 2; h++) {
            const int n0 = 8 * i + 2 * c;
            acc[4 * i + 2 * h] += __uint_as_float(lds32(zrow + h * 2048 + ((n0 ^ zsw) << 2)));
            if (i < 7 || c < 3) acc[4 * i + 2 * h + 1] += __uint_as_float(lds32(zrow + h * 2048 + (((n0 + 1) ^ zsw) << 2)));
          }
        }
        {
          const uint32_t yf = sb + OFF_WB + (ci < 2 ? wg : 1) * WB_BYTES;
#pragma unroll
          for (int e = 0; e < 2; e++) {
#pragma unroll
            for (int h = 0; h < 2; h++) {
              const int word = (32 * (31 - 2 * c - e) + 16 * w + 8 * h + r) ^ (((3 - c) & 3) << 3);
#pragma unroll
              for (int i = 0; i < 4; i++) acc[4 * i + 2 * h + e] += __uint_as_float(lds32(yf + word * 4 - 1024 * i));
            }
          }
        }
        const uint32_t ys = (sb + OFF_Q + ch * Q_BYTES + 1023u) & ~1023u;
        const int mi = lane >> 3, jj = lane & 7;
#pragma unroll
        for (int i = 0; i < 8; i += 2) {
          const int a = 63 - 8 * (i + (mi >> 1)) - jj;
          const int pi = 4 * a + 2 * w + (mi & 1);
          stsm4t(ys + ((pi ^ ((pi >> 3) & 7)) << 4), pack_bf16(acc[4 * i], acc[4 * i + 1]), pack_bf16(acc[4 * i + 2], acc[4 * i + 3]),
                 pack_bf16(acc[4 * i + 4], acc[4 * i + 5]), pack_bf16(acc[4 * i + 6], acc[4 * i + 7]));
        }
        fence_async_smem();
        named_sync(4 + wg, 64);
        if (w == 0 && lane == 0) {
          tma_st2(&tm_ast, ys, 0, d * 32);
          bulk_commit();
        }
      }
      named_sync(2 + wg, 128);
      }
    }
    if (w == 0 && lane == 0) {
      bulk_wait_all();
      cnt_arrive_after_bulk(CNT_A + (cta >> 5));
      mbar_arrive(BAR(BAR_CONVDONE + wg));
    }
    TSTAMP(40 + warp);
    }
  }
  __syncwarp();
  asm volatile("barrier.cluster.arrive.relaxed.aligned;\nbarrier.cluster.wait.aligned;" ::: "memory");
  if (warp == 0) { TSTAMP(66); GSTAMP(67); }
}

typedef CUresult (*EncodeFn)(CUtensorMap*, CUtensorMapDataType, cuuint32_t, void*, const cuuint64_t*, const cuuint64_t*,
                             const cuuint32_t*, const cuuint32_t*, CUtensorMapInterleave, CUtensorMapSwizzle,
                             CUtensorMapL2promotion, CUtensorMapFloatOOBfill);

void make_map(EncodeFn fn, CUtensorMap* m, const void* ptr, int rank, const cuuint64_t* dims, const cuuint64_t* strides,
              const cuuint32_t* box, CUtensorMapSwizzle swz) {
  cuuint32_t es[5] = {1, 1, 1, 1, 1};
  fn(m, CU_TENSOR_MAP_DATA_TYPE_BFLOAT16, rank, const_cast<void*>(ptr), dims, strides, box, es, CU_TENSOR_MAP_INTERLEAVE_NONE,
     swz, CU_TENSOR_MAP_L2_PROMOTION_L2_128B, CU_TENSOR_MAP_FLOAT_OOB_FILL_NONE);
}

}

extern "C" void kernel_launch(void* const* d_in, const int* in_sizes, int n_in, void* d_out, int out_size) {
  (void)in_sizes; (void)n_in; (void)out_size;
  static EncodeFn enc = nullptr;
  static void *p_h = nullptr, *p_aT = nullptr;
  if (!enc) {
    void* f = nullptr;
    cudaDriverEntryPointQueryResult qr;
    cudaGetDriverEntryPoint("cuTensorMapEncodeTiled", &f, cudaEnableDefault, &qr);
    enc = (EncodeFn)f;
    cudaGetSymbolAddress(&p_h, g_h);
    cudaGetSymbolAddress(&p_aT, g_aT);
    cudaFuncSetAttribute(fused_kernel, cudaFuncAttributeMaxDynamicSharedMemorySize, SMEM_BYTES);
  }
  const __nv_bfloat16* u = (const __nv_bfloat16*)d_in[0];
  const __nv_bfloat16* w1 = (const __nv_bfloat16*)d_in[8];
  const __nv_bfloat16* w2 = (const __nv_bfloat16*)d_in[9];
  CUtensorMap tm_x, tm_w1a, tm_w1b, tm_slab, tm_hst, tm_hld, tm_w2, tm_aT, tm_ast, tm_out;
  {
    cuuint64_t dims[2] = {D_, L_}, st[1] = {D_ * 2};
    cuuint32_t box[2] = {64, 128};
    make_map(enc, &tm_x, u, 2, dims, st, box, CU_TENSOR_MAP_SWIZZLE_128B);
    cuuint64_t dims4[4] = {64, 32, 64, 10}, st4[3] = {D_ * 2, 32 * D_ * 2, 128};
    cuuint32_t box4[4] = {64, 8, 2, 10};
    make_map(enc, &tm_slab, u, 4, dims4, st4, box4, CU_TENSOR_MAP_SWIZZLE_128B);
    cuuint32_t boxo[2] = {80, 64};
    make_map(enc, &tm_out, d_out, 2, dims, st, boxo, CU_TENSOR_MAP_SWIZZLE_NONE);
  }
  {
    cuuint64_t dims[3] = {32, D_, F_ / 32}, st[2] = {F_ * 2, 64};
    cuuint32_t box4[3] = {32, 32, 4}, box3[3] = {32, 32, 3};
    make_map(enc, &tm_w1a, w1, 3, dims, st, box4, CU_TENSOR_MAP_SWIZZLE_64B);
    make_map(enc, &tm_w1b, w1, 3, dims, st, box3, CU_TENSOR_MAP_SWIZZLE_64B);
  }
  {
    cuuint64_t dims[2] = {F_, L_}, st[1] = {F_ * 2};
    cuuint32_t boxl[2] = {64, 64};
    cuuint64_t dims3[3] = {32, L_, F_ / 32}, st3[2] = {F_ * 2, 64};
    cuuint32_t boxs[3] = {32, 64, 7};
    make_map(enc, &tm_hst, p_h, 3, dims3, st3, boxs, CU_TENSOR_MAP_SWIZZLE_64B);
    make_map(enc, &tm_hld, p_h, 2, dims, st, boxl, CU_TENSOR_MAP_SWIZZLE_128B);
  }
  {
    cuuint64_t dims[4] = {32, F_, 5, 4}, st[3] = {D_ * 2, 64, 320};
    cuuint32_t box[4] = {32, 32, 5, 1};
    make_map(enc, &tm_w2, w2, 4, dims, st, box, CU_TENSOR_MAP_SWIZZLE_64B);
  }
  {
    cuuint64_t dims[2] = {L_, D_}, st[1] = {L_ * 2};
    cuuint32_t box[2] = {64, 80};
    make_map(enc, &tm_aT, p_aT, 2, dims, st, box, CU_TENSOR_MAP_SWIZZLE_128B);
    cuuint64_t dims2[2] = {64, D_ * 32}, st2[1] = {128};
    cuuint32_t box2[2] = {64, 32};
    make_map(enc, &tm_ast, p_aT, 2, dims2, st2, box2, CU_TENSOR_MAP_SWIZZLE_128B);
  }
  Ptrs P;
  P.u = u;
  P.logA = (const __nv_bfloat16*)d_in[1];
  P.Aim = (const __nv_bfloat16*)d_in[2];
  P.Cre = (const __nv_bfloat16*)d_in[3];
  P.Cim = (const __nv_bfloat16*)d_in[4];
  P.logdt = (const __nv_bfloat16*)d_in[5];
  P.Dskip = (const __nv_bfloat16*)d_in[6];
  P.gatew = (const __nv_bfloat16*)d_in[10];
  P.w1 = w1;
  P.w2 = w2;
  fused_kernel<<<NCTA, NTHREADS, SMEM_BYTES>>>(tm_x, tm_w1a, tm_w1b, tm_slab, tm_hst, tm_hld, tm_w2, tm_aT, tm_ast, tm_out, P);
}
```
